```python
import torch

def _softmax(x, axis=-1):
    return torch.softmax(x, dim=axis)

def _gelu(x):
    return torch.nn.functional.gelu(x, approximate='tanh')

def _silu(x):
    return torch.nn.functional.silu(x)

def _sigmoid(x):
    return torch.sigmoid(x)

def _layernorm(x, axis=-1, eps=1e-05):
    m = x.mean(dim=axis, keepdim=True)
    v = x.var(dim=axis, keepdim=True, unbiased=False)
    return (x - m) / torch.sqrt(v + eps)

def _scatter_add(tgt, idx, src, axis=0):
    return tgt.clone().index_add_(axis, idx, src)

def _segment_sum(src, seg, n):
    out = torch.zeros((n,) + src.shape[1:], dtype=src.dtype)
    return out.index_add_(0, seg, src)

def _pad(x, pw):
    flat = tuple((v for pair in reversed(pw) for v in pair))
    return torch.nn.functional.pad(x, flat)
kernel_name = 'adaLN_cond__compressed_kv_cla__dense_activation_gelu__decode'

def setup_inputs():

    _w = lambda a: (lambda t: t.to(torch.bfloat16) if t.is_floating_point() else t)(torch.as_tensor(a))

    def _A_setup():
        B, H, Sq, Sk, D, M = (1, 32, 1, 8192, 128, 512)
        Dc = 4 * D
        return {'x': _w((lambda *s: torch.randn(*s, dtype=torch.bfloat16) * 0.1)(B, Sq, M)), 'c_kv': _w((lambda *s: torch.randn(*s, dtype=torch.bfloat16) * 3.2)(B, Sk, Dc)), 'w_q': _w((lambda *s: torch.randn(*s, dtype=torch.bfloat16) * 0.8)(M, H, D) * M ** (-0.5)), 'w_uk': _w((lambda *s: torch.randn(*s, dtype=torch.bfloat16) * 0.8)(Dc, H, D) * Dc ** (-0.5)), 'w_uv': _w((lambda *s: torch.randn(*s, dtype=torch.bfloat16) * 3.2)(Dc, H, D) * Dc ** (-0.5)), 'w_o': _w((lambda *s: torch.randn(*s, dtype=torch.bfloat16) * 3.2)(H, D, M) * (H * D) ** (-0.5))}
    _A_in = _A_setup()

    def _B_setup():
        B, S, D, F = (1, 1, 512, 1376)
        return {'x': _w((lambda *s: torch.randn(*s, dtype=torch.bfloat16) * 0.1)(B, S, D)), 'w1': _w((lambda *s: torch.randn(*s, dtype=torch.bfloat16) * 3.2)(D, F) * D ** (-0.5)), 'b1': _w((lambda *s: torch.randn(*s, dtype=torch.bfloat16) * 3.2)(F) * 0.01), 'w2': _w((lambda *s: torch.randn(*s, dtype=torch.bfloat16) * 3.2)(F, D) * F ** (-0.5)), 'b2': _w((lambda *s: torch.randn(*s, dtype=torch.bfloat16) * 3.2)(D) * 0.01)}
    _B_in = _B_setup()
    return {'A_x': _A_in['x'], 'A_c_kv': _A_in['c_kv'], 'A_w_q': _A_in['w_q'], 'A_w_uk': _A_in['w_uk'], 'A_w_uv': _A_in['w_uv'], 'A_w_o': _A_in['w_o'], 'B_x': _B_in['x'], 'B_w1': _B_in['w1'], 'B_b1': _B_in['b1'], 'B_w2': _B_in['w2'], 'B_b2': _B_in['b2'], 'c': _w((lambda *s: torch.randn(*s, dtype=torch.bfloat16) * 0.1)(1, 512) * 8.0), 'w_mod': _w((lambda *s: torch.randn(*s, dtype=torch.bfloat16) * 0.1)(512, 6 * 512) * 512 ** (-0.5) * 8.0)}

def reference(A_x, A_c_kv, A_w_q, A_w_uk, A_w_uv, A_w_o, B_x, B_w1, B_b1, B_w2, B_b2, c, w_mod):

    def _A_ref(x, c_kv, w_q, w_uk, w_uv, w_o):
        B, Sq, M = (x.shape[0], x.shape[1], x.shape[2])
        Sk = c_kv.shape[1]
        H, D = (w_q.shape[1], w_q.shape[2])
        q = torch.einsum('bqm,mhd->bhqd', x, w_q)
        k = torch.einsum('bkc,chd->bhkd', c_kv, w_uk)
        v = torch.einsum('bkc,chd->bhkd', c_kv, w_uv)
        scores = torch.einsum('bhqd,bhkd->bhqk', q, k) * D ** (-0.5)
        off = Sk - Sq
        qi = torch.arange(Sq)[:, None]
        kj = torch.arange(Sk)[None, :]
        cmask = kj <= qi + off
        scores = torch.where(cmask[None, None], scores, -1000000000.0)
        p = _softmax(scores, axis=-1)
        ctx = torch.einsum('bhqk,bhkd->bhqd', p, v)
        return torch.einsum('bhqd,hdm->bqm', ctx, w_o)

    def _B_ref(x, w1, b1, w2, b2):
        h = torch.einsum('bsd,df->bsf', x, w1) + b1
        h = _gelu(h)
        return torch.einsum('bsf,fd->bsd', h, w2) + b2
    x = A_x
    mod = (_silu(c) @ w_mod).reshape(c.shape[0], 6, 1, -1)
    sa, ca, ga, sb, cb, gb = (mod[:, 0].clone(), mod[:, 1].clone(), mod[:, 2].clone(), mod[:, 3].clone(), mod[:, 4].clone(), mod[:, 5].clone())
    h = _layernorm(x, axis=-1) * (1 + ca) + sa
    x = x + ga * _A_ref(h, A_c_kv, A_w_q, A_w_uk, A_w_uv, A_w_o)
    h = _layernorm(x, axis=-1) * (1 + cb) + sb
    x = x + gb * _B_ref(h, B_w1, B_b1, B_w2, B_b2)
    return x
```

```cpp
#include <cuda_runtime.h>
#include <cuda_bf16.h>
#include <cuda.h>
#include <stdint.h>

namespace {

constexpr int NCTA   = 128;
constexpr int NFFN   = 86;
constexpr int NCHUNK = 32;
constexpr int NTHR   = 384;

constexpr int C_MOD1 = 0, C_WQ = 1, C_WUK = 5, C_CKV = 9, C_X = 17, C_WUV = 18, C_MOD2 = 22, C_WO = 24, C_W1 = 28, C_W2 = 30;

constexpr int S_WQ   = 0;
constexpr int S_WUK  = 32768;
constexpr int S_CKV  = 65536;
constexpr int S_WUV  = 131072;
constexpr int S_WO   = 163840;
constexpr int S_MOD2 = 196608;
constexpr int S_MOD1 = 212992;
constexpr int S_SC   = 221184;
constexpr int S_RED  = 223232;
constexpr int S_VEC  = 227328;
constexpr int S_R16  = 227840;
constexpr int S_MAX  = 228352;
constexpr int S_ONES = 229376;
constexpr int S_ML   = 230400;
constexpr int S_STAT = 230912;
constexpr int S_BAR  = 230976;
constexpr int S_EP   = 231312;
constexpr int S_B4   = 230912;
constexpr int S_TS   = 231328;
constexpr int S_END  = 231712;
constexpr int S_QABS = S_WQ, S_XBUF1 = S_WQ + 20480, S_XBUF0 = S_MOD1, S_XCH = S_WUK, S_GVEC = S_WQ, S_FVEC = S_WQ + 8192;
constexpr int S_W1 = S_WUK, S_W2 = S_WUK + 16384, S_P = S_MOD1, S_ALPHA = S_R16;
constexpr int B_UK = 32, B_QK = 33, B_X = 34, B_F = 36, B_BETA = 37, B_BETA4 = 38, B_W = 39, B_L = 40, NBAR = 41;
constexpr int SMEM_BYTES = S_END;

#define POLMASK 0
#define KEEP_NS 200
#define KEEP_TAIL 2
#define WIN 5
enum { T_H1 = 0, T_H3, T_H4, D_H5, D_H6, D_H7, D_H4, D_ML, NTM = 8 };

constexpr uint32_t G_H1 = 0;
constexpr uint32_t G_H6 = 16 << 10;
constexpr uint32_t G_MOD2 = 32 << 10;
constexpr uint32_t G_ML = 48 << 10;
constexpr uint32_t G_PROBE = 88 << 10;
constexpr uint32_t G_H3 = 128 << 10;
constexpr uint32_t G_H2 = 256 << 10;
constexpr uint32_t G_H5 = 384 << 10;
constexpr uint32_t G_H7 = 512 << 10;
constexpr uint32_t G_EPOCH = 1 << 20;
constexpr uint32_t G_TS = (1 << 20) + 4096;
constexpr uint32_t G_H4 = 2 << 20;
constexpr uint32_t G_BYTES = 10 << 20;
__device__ __align__(256) unsigned char g_scratch[G_BYTES + (2 << 20)];
__device__ __forceinline__ uint32_t spread(uint32_t o) { return o + (o & ~4095u); }
__device__ __forceinline__ uint32_t pick(uint32_t po, uint32_t beta) {
    return po + (((beta ^ __popc(po & 0xB2000u)) & 1u) << 12);
}
#define TS(i) do {} while (0)
#define TS0(i) do {} while (0)
#define TS4(i) do {} while (0)

struct Params {
    const __nv_bfloat16* x;
    const __nv_bfloat16* c;
    const __nv_bfloat16* b1;
    const __nv_bfloat16* b2;
    __nv_bfloat16* out;
    unsigned char* s;
    uint16_t tm[NTM];
    uint16_t sched[32];
    CUtensorMap m[8];
};

constexpr int SPIN_MAX = 1 << 21;

__device__ __forceinline__ void mbar_init(uint32_t bar, uint32_t cnt) {
    asm volatile("mbarrier.init.shared::cta.b64 [%0], %1;" ::"r"(bar), "r"(cnt) : "memory");
}
__device__ __forceinline__ void mbar_expect_tx(uint32_t bar, uint32_t bytes) {
    asm volatile("mbarrier.arrive.expect_tx.shared::cta.b64 _, [%0], %1;" ::"r"(bar), "r"(bytes) : "memory");
}
__device__ __forceinline__ void mbar_arrive(uint32_t bar) {
    asm volatile("mbarrier.arrive.shared::cta.b64 _, [%0];" ::"r"(bar) : "memory");
}
__device__ __forceinline__ void mbar_wait(uint32_t bar) {
    asm volatile("{\n.reg .pred p;\nW:\nmbarrier.try_wait.parity.shared::cta.b64 p, [%0], 0;\n@!p bra W;\n}" ::"r"(bar) : "memory");
}
__device__ __forceinline__ void mbar_wait4(uint32_t bar) {
    asm volatile("{\n.reg .pred p, q, r, s;\nW:\n"
                 "mbarrier.try_wait.parity.shared::cta.b64 p, [%0], 0;\n"
                 "mbarrier.try_wait.parity.shared::cta.b64 q, [%0+8], 0;\n"
                 "mbarrier.try_wait.parity.shared::cta.b64 r, [%0+16], 0;\n"
                 "mbarrier.try_wait.parity.shared::cta.b64 s, [%0+24], 0;\n"
                 "and.pred p, p, q;\nand.pred r, r, s;\nand.pred p, p, r;\n@!p bra W;\n}" ::"r"(bar) : "memory");
}
__device__ __forceinline__ void mbar_wait_cluster(uint32_t bar) {
    asm volatile("{\n.reg .pred p;\nW:\nmbarrier.try_wait.parity.acquire.cluster.shared::cta.b64 p, [%0], 0;\n@!p bra W;\n}" ::"r"(bar) : "memory");
}
__device__ __forceinline__ void tma4(uint32_t dst, const CUtensorMap* m, int c0, int c1, int c2, int c3, uint32_t bar, uint64_t pol) {
    asm volatile("cp.async.bulk.tensor.4d.shared::cluster.global.mbarrier::complete_tx::bytes.L2::cache_hint [%0], [%1, {%3,%4,%5,%6}], [%2], %7;"
                 ::"r"(dst), "l"(m), "r"(bar), "r"(c0), "r"(c1), "r"(c2), "r"(c3), "l"(pol) : "memory");
}
__device__ __forceinline__ void bar_sync(int id, int n) { asm volatile("bar.sync %0, %1;" ::"r"(id), "r"(n) : "memory"); }
__device__ __forceinline__ void bar_arrive(int id, int n) { asm volatile("bar.arrive %0, %1;" ::"r"(id), "r"(n) : "memory"); }
__device__ __forceinline__ void fence_async() { asm volatile("fence.proxy.async.shared::cta;" ::: "memory"); }

__device__ __forceinline__ uint32_t ldr1(const void* p) {
    uint32_t v; asm volatile("ld.relaxed.gpu.global.u32 %0, [%1];" : "=r"(v) : "l"(p) : "memory"); return v;
}
__device__ __forceinline__ uint2 ldr2(const void* p) {
    uint2 v; asm volatile("ld.relaxed.gpu.global.v2.u32 {%0,%1}, [%2];" : "=r"(v.x), "=r"(v.y) : "l"(p) : "memory"); return v;
}
__device__ __forceinline__ uint4 ldr4(const void* p) {
    uint4 v; asm volatile("ld.relaxed.gpu.global.v4.u32 {%0,%1,%2,%3}, [%4];"
                          : "=r"(v.x), "=r"(v.y), "=r"(v.z), "=r"(v.w) : "l"(p) : "memory"); return v;
}
__device__ __forceinline__ void str1(void* p, uint32_t v) { asm volatile("st.relaxed.gpu.global.u32 [%0], %1;" ::"l"(p), "r"(v) : "memory"); }
__device__ __forceinline__ void str2(void* p, uint32_t a, uint32_t b) {
    asm volatile("st.relaxed.gpu.global.v2.u32 [%0], {%1,%2};" ::"l"(p), "r"(a), "r"(b) : "memory");
}
__device__ __forceinline__ void str4(void* p, uint32_t a, uint32_t b, uint32_t c, uint32_t d) {
    asm volatile("st.relaxed.gpu.global.v4.u32 [%0], {%1,%2,%3,%4};" ::"l"(p), "r"(a), "r"(b), "r"(c), "r"(d) : "memory");
}
__device__ __forceinline__ void str64(void* p, uint32_t a, uint32_t b) {
    asm volatile("{\n.reg .b64 t;\nmov.b64 t, {%1,%2};\nst.relaxed.gpu.global.b64 [%0], t;\n}" ::"l"(p), "r"(a), "r"(b) : "memory");
}
__device__ __forceinline__ void str64x2(void* p, uint32_t a, uint32_t b, uint32_t c, uint32_t d) {
    asm volatile("{\n.reg .b64 s, t;\nmov.b64 s, {%1,%2};\nmov.b64 t, {%3,%4};\nst.relaxed.gpu.global.v2.b64 [%0], {s,t};\n}" ::"l"(p), "r"(a), "r"(b), "r"(c), "r"(d) : "memory");
}
__device__ __forceinline__ uint4 ldr64x2(const void* p) {
    uint4 v; asm volatile("{\n.reg .b64 s, t;\nld.relaxed.gpu.global.v2.b64 {s,t}, [%4];\nmov.b64 {%0,%1}, s;\nmov.b64 {%2,%3}, t;\n}"
                          : "=r"(v.x), "=r"(v.y), "=r"(v.z), "=r"(v.w) : "l"(p) : "memory"); return v;
}
__device__ __forceinline__ uint32_t tagf(float v, uint32_t tg) { return (__float_as_uint(v) & ~1u) | tg; }
__device__ __forceinline__ float u2f(uint32_t v) { return __uint_as_float(v); }

__device__ __forceinline__ void sts1(uint32_t a, uint32_t v) { asm volatile("st.shared.u32 [%0], %1;" ::"r"(a), "r"(v) : "memory"); }
__device__ __forceinline__ void sts1f(uint32_t a, float v) { asm volatile("st.shared.f32 [%0], %1;" ::"r"(a), "f"(v) : "memory"); }
__device__ __forceinline__ void stsh(uint32_t a, uint32_t v) { asm volatile("st.shared.u16 [%0], %1;" ::"r"(a), "h"((unsigned short)v) : "memory"); }
__device__ __forceinline__ void sts2(uint32_t a, uint32_t x, uint32_t y) { asm volatile("st.shared.v2.u32 [%0], {%1,%2};" ::"r"(a), "r"(x), "r"(y) : "memory"); }
__device__ __forceinline__ void sts4(uint32_t a, uint32_t x, uint32_t y, uint32_t z, uint32_t w) {
    asm volatile("st.shared.v4.u32 [%0], {%1,%2,%3,%4};" ::"r"(a), "r"(x), "r"(y), "r"(z), "r"(w) : "memory");
}
__device__ __forceinline__ uint32_t lds1(uint32_t a) { uint32_t v; asm volatile("ld.shared.u32 %0, [%1];" : "=r"(v) : "r"(a) : "memory"); return v; }
__device__ __forceinline__ float lds1f(uint32_t a) { float v; asm volatile("ld.shared.f32 %0, [%1];" : "=f"(v) : "r"(a) : "memory"); return v; }
__device__ __forceinline__ float2 lds2f(uint32_t a) { float2 v; asm volatile("ld.shared.v2.f32 {%0,%1}, [%2];" : "=f"(v.x), "=f"(v.y) : "r"(a) : "memory"); return v; }
__device__ __forceinline__ uint4 lds4(uint32_t a) {
    uint4 v; asm volatile("ld.shared.v4.u32 {%0,%1,%2,%3}, [%4];" : "=r"(v.x), "=r"(v.y), "=r"(v.z), "=r"(v.w) : "r"(a) : "memory"); return v;
}
__device__ __forceinline__ float4 lds4f(uint32_t a) {
    float4 v; asm volatile("ld.shared.v4.f32 {%0,%1,%2,%3}, [%4];" : "=f"(v.x), "=f"(v.y), "=f"(v.z), "=f"(v.w) : "r"(a) : "memory"); return v;
}
__device__ __forceinline__ void ldsm4(uint32_t a, uint32_t (&r)[4]) {
    asm volatile("ldmatrix.sync.aligned.m8n8.x4.shared.b16 {%0,%1,%2,%3}, [%4];"
                 : "=r"(r[0]), "=r"(r[1]), "=r"(r[2]), "=r"(r[3]) : "r"(a) : "memory");
}
__device__ __forceinline__ void ldsm4t(uint32_t a, uint32_t (&r)[4]) {
    asm volatile("ldmatrix.sync.aligned.m8n8.x4.trans.shared.b16 {%0,%1,%2,%3}, [%4];"
                 : "=r"(r[0]), "=r"(r[1]), "=r"(r[2]), "=r"(r[3]) : "r"(a) : "memory");
}
__device__ __forceinline__ void stsm4t(uint32_t a, uint32_t r0, uint32_t r1, uint32_t r2, uint32_t r3) {
    asm volatile("stmatrix.sync.aligned.m8n8.x4.trans.shared.b16 [%0], {%1,%2,%3,%4};"
                 ::"r"(a), "r"(r0), "r"(r1), "r"(r2), "r"(r3) : "memory");
}
__device__ __forceinline__ void mma16816(float (&d)[4], const uint32_t (&a)[4], uint32_t b0, uint32_t b1) {
    asm volatile("mma.sync.aligned.m16n8k16.row.col.f32.bf16.bf16.f32 {%0,%1,%2,%3}, {%4,%5,%6,%7}, {%8,%9}, {%0,%1,%2,%3};"
                 : "+f"(d[0]), "+f"(d[1]), "+f"(d[2]), "+f"(d[3])
                 : "r"(a[0]), "r"(a[1]), "r"(a[2]), "r"(a[3]), "r"(b0), "r"(b1));
}
__device__ __forceinline__ uint32_t packbf(float lo, float hi) {
    uint32_t r; asm("cvt.rn.bf16x2.f32 %0, %1, %2;" : "=r"(r) : "f"(hi), "f"(lo)); return r;
}
__device__ __forceinline__ float bflo(uint32_t w) { return __uint_as_float(w << 16); }
__device__ __forceinline__ float bfhi(uint32_t w) { return __uint_as_float(w & 0xffff0000u); }
__device__ __forceinline__ void split2(float a, float b, uint32_t& hi, uint32_t& lo) {
    hi = packbf(a, b);
    lo = packbf(a - bflo(hi), b - bfhi(hi));
}
__device__ __forceinline__ float ex2(float x) { float y; asm("ex2.approx.ftz.f32 %0, %1;" : "=f"(y) : "f"(x)); return y; }

__device__ __forceinline__ int vpos(int k32) {
    return (((k32 & 7) >> 1) * 8 + (k32 >> 4) * 4 + ((k32 >> 3) & 1) * 2 + (k32 & 1)) * 2;
}

__device__ __forceinline__ void wg_fence()  { asm volatile("wgmma.fence.sync.aligned;" ::: "memory"); }
__device__ __forceinline__ void wg_commit() { asm volatile("wgmma.commit_group.sync.aligned;" ::: "memory"); }
template <int N> __device__ __forceinline__ void wg_wait() { asm volatile("wgmma.wait_group.sync.aligned %0;" ::"n"(N) : "memory"); }
__device__ __forceinline__ uint64_t mkdesc(uint32_t addr) {
    return (uint64_t)((addr & 0x3FFFF) >> 4) | ((uint64_t)64 << 16) | ((uint64_t)64 << 32) | ((uint64_t)1 << 62);
}
template <int TA>
__device__ __forceinline__ void wgmma_n32(float (&d)[16], uint64_t da, uint64_t db, int acc) {
    asm volatile("{\n.reg .pred p;\nsetp.ne.b32 p, %18, 0;\n"
                 "wgmma.mma_async.sync.aligned.m64n32k16.f32.bf16.bf16 "
                 "{%0,%1,%2,%3,%4,%5,%6,%7,%8,%9,%10,%11,%12,%13,%14,%15}, %16, %17, p, 1, 1, %19, 0;\n}"
                 : "+f"(d[0]), "+f"(d[1]), "+f"(d[2]), "+f"(d[3]), "+f"(d[4]), "+f"(d[5]), "+f"(d[6]), "+f"(d[7]),
                   "+f"(d[8]), "+f"(d[9]), "+f"(d[10]), "+f"(d[11]), "+f"(d[12]), "+f"(d[13]), "+f"(d[14]), "+f"(d[15])
                 : "l"(da), "l"(db), "r"(acc), "n"(TA));
}
__device__ __forceinline__ void reg_fence16(float (&d)[16]) {
#pragma unroll
    for (int i = 0; i < 16; i++) asm volatile("" : "+f"(d[i])::"memory");
}

template <bool TRANS>
__device__ __forceinline__ void gemv128(uint32_t tile, uint32_t vec, uint32_t bars, int warp, int lane, float& r0, float& r1) {
    const int m = lane >> 3, r8 = lane & 7;
    uint32_t bq[4][4];
#pragma unroll
    for (int i = 0; i < 4; i++) {
        uint4 t = lds4(vec + i * 128 + ((lane >> 2) & 1) * 64 + (lane & 3) * 16);
        bq[i][0] = t.x; bq[i][1] = t.y; bq[i][2] = t.z; bq[i][3] = t.w;
    }
    float d0[4] = {0.f, 0.f, 0.f, 0.f}, d1[4] = {0.f, 0.f, 0.f, 0.f};
    if (TRANS) {
        const uint32_t a0 = tile + (warp >> 2) * 4096 + ((m >> 1) * 8 + r8) * 128 + ((((warp & 3) * 2 + (m & 1)) ^ r8) << 4);
#pragma unroll
        for (int i = 0; i < 4; i++) {
            mbar_wait(bars + i * 8);
            uint32_t a[4], c[4];
            ldsm4t(a0 + i * 8192, a);
            ldsm4t(a0 + i * 8192 + 2048, c);
            mma16816(d0, a, bq[i][0], bq[i][1]);
            mma16816(d1, c, bq[i][2], bq[i][3]);
        }
    } else {
        mbar_wait(bars + (warp >> 1) * 8);
        const uint32_t a0 = tile + (warp >> 1) * 8192 + ((warp & 1) * 16 + (m & 1) * 8 + r8) * 128;
#pragma unroll
        for (int i = 0; i < 4; i++) {
            uint32_t a[4], c[4];
            ldsm4(a0 + (i >> 1) * 4096 + ((((i & 1) * 4 + (m >> 1)) ^ r8) << 4), a);
            ldsm4(a0 + (i >> 1) * 4096 + ((((i & 1) * 4 + 2 + (m >> 1)) ^ r8) << 4), c);
            mma16816(d0, a, bq[i][0], bq[i][1]);
            mma16816(d1, c, bq[i][2], bq[i][3]);
        }
    }
    r0 = (d0[0] + d0[1]) + (d1[0] + d1[1]);
    r1 = (d0[2] + d0[3]) + (d1[2] + d1[3]);
}

__device__ __forceinline__ void step32(uint32_t rows, uint32_t vecaddr, int lane, float (&d0)[4], float (&d1)[4]) {
    const int m = lane >> 3, r8 = lane & 7;
    const uint32_t a0 = rows + ((m >> 1) * 8 + r8) * 32 + (((m & 1) ^ (r8 >> 2)) << 4);
    uint4 t = lds4(vecaddr);
    uint32_t a[4], c[4];
    ldsm4t(a0, a);
    ldsm4t(a0 + 512, c);
    mma16816(d0, a, t.x, t.y);
    mma16816(d1, c, t.z, t.w);
}

__device__ __forceinline__ void reduce16_publish(uint32_t sb, float (&d0)[4], float (&d1)[4], int tid, int warp, int lane, unsigned char* dst, uint32_t tg) {
    if ((lane & 3) == 0) {
        sts1f(sb + S_R16 + (lane >> 2) * 32 + warp * 4, (d0[0] + d0[1]) + (d1[0] + d1[1]));
        sts1f(sb + S_R16 + ((lane >> 2) + 8) * 32 + warp * 4, (d0[2] + d0[3]) + (d1[2] + d1[3]));
    }
    bar_sync(2, 256);
    if (tid < 32) {
        float4 u = lds4f(sb + S_R16 + (tid & 15) * 32), v = lds4f(sb + S_R16 + (tid & 15) * 32 + 16);
        str1(dst + (tid & 15) * 4 + (tid >> 4) * 4096, tagf(((u.x + u.y) + (u.z + u.w)) + ((v.x + v.y) + (v.z + v.w)), tg));
    }
}

__device__ __forceinline__ uint32_t xo2(uint32_t a, uint32_t b, uint32_t t) {
    uint32_t r; asm("lop3.b32 %0, %1, %2, %3, 0x7E;" : "=r"(r) : "r"(a), "r"(b), "r"(t)); return r;
}
__device__ __forceinline__ uint32_t or3(uint32_t a, uint32_t b, uint32_t c) {
    uint32_t r; asm("lop3.b32 %0, %1, %2, %3, 0xFE;" : "=r"(r) : "r"(a), "r"(b), "r"(c)); return r;
}
__device__ __forceinline__ uint32_t bad2(const uint2& v, uint32_t tg) { return xo2(v.x, v.y, tg); }
__device__ __forceinline__ uint32_t bad4(const uint4& v, uint32_t tg) { return xo2(v.x, v.y, tg) | xo2(v.z, v.w, tg); }
__device__ __forceinline__ bool nz4(const uint4& v) { return v.x != 0 && v.y != 0 && v.z != 0 && v.w != 0; }
__device__ __forceinline__ uint32_t clk32() { uint32_t c; asm volatile("mov.u32 %0, %%clock;" : "=r"(c)); return c; }
__device__ __forceinline__ void wait_until(uint32_t t0, uint32_t dt) {
#pragma unroll 1
    while (clk32() - t0 < dt) {}
}
__device__ __forceinline__ uint32_t mbar_mask4(uint32_t bar) {
    uint32_t m;
    asm volatile("{\n.reg .pred p, q, r, s;\n.reg .b32 a, b;\n"
                 "mbarrier.test_wait.parity.shared::cta.b64 p, [%1], 0;\n"
                 "mbarrier.test_wait.parity.shared::cta.b64 q, [%1+8], 0;\n"
                 "mbarrier.test_wait.parity.shared::cta.b64 r, [%1+16], 0;\n"
                 "mbarrier.test_wait.parity.shared::cta.b64 s, [%1+24], 0;\n"
                 "selp.u32 a, 1, 0, p;\nselp.u32 b, 2, 0, q;\nor.b32 a, a, b;\nselp.u32 b, 4, 0, r;\nor.b32 a, a, b;\n"
                 "selp.u32 b, 8, 0, s;\nor.b32 a, a, b;\nredux.sync.and.b32 %0, a, 0xffffffff;\n}" : "=r"(m) : "r"(bar) : "memory");
    return m;
}
__device__ __forceinline__ uint32_t probe_near(unsigned char* sp, uint32_t po, uint32_t sink) {
    uint32_t best0 = ~0u, best1 = ~0u;
#pragma unroll 1
    for (int r = 0; r < 5; r++) {
        uint32_t v; const uint32_t t0 = clk32();
        asm volatile("atom.relaxed.gpu.global.exch.b32 %0, [%1], %2;" : "=r"(v) : "l"(sp + po + (r & 1) * 4096), "r"(r) : "memory");
        sts1(sink, v);
        const uint32_t dt = clk32() - t0;
        if (r & 1) best1 = min(best1, dt); else best0 = min(best0, dt);
    }
    return (uint32_t)(best1 < best0) ^ (__popc(po & 0xB2000u) & 1u);
}
#define mbar_wait_init(sb) bar_sync(8, 64)
#define SPIN_CHECK(it) if (++(it) > SPIN_MAX) __trap()

__global__ void __cluster_dims__(2, 1, 1) __launch_bounds__(NTHR, 1) fused_decode_kernel(const __grid_constant__ Params p) {
    extern __shared__ __align__(1024) unsigned char smem_raw[];
    const uint32_t sb = (uint32_t)__cvta_generic_to_shared(smem_raw);
    const int tid = threadIdx.x, lane = tid & 31;
    const int warp = __shfl_sync(~0u, tid >> 5, 0);
    const int b = blockIdx.x, h = b >> 2, j = b & 3, rank = b & 1, pair = b >> 1;
    const uint32_t bars = sb + S_BAR;
    unsigned char* const sp = p.s;
    const uint32_t t_start = clk32();

    if (warp == 11) {
        float d[4] = {0.f, 0.f, 0.f, 0.f};
        const uint32_t zz = t_start & 0x00010001u, z[4] = {zz, zz, zz, zz};
        mma16816(d, z, zz, zz);
        bar_sync(1, NTHR - 32);
        uint32_t done = 0;
#pragma unroll 1
        for (int i = 0; i < 4096 && done < KEEP_TAIL; i++) {
            mma16816(d, z, zz, zz);
            __nanosleep(KEEP_NS);
            done += mbar_mask4(bars + B_F * 8) & 1;
        }
        if (d[0] == 1.f) sts1f(sb + S_EP + 12, d[1]);
        return;
    }
    if (warp == 8) {
        TS(30);
        uint64_t pol_first, pol_norm;
        asm("createpolicy.fractional.L2::evict_first.b64 %0, 1.0;" : "=l"(pol_first));
        asm("createpolicy.fractional.L2::evict_normal.b64 %0, 1.0;" : "=l"(pol_norm));
        if (lane == 0) {
            mbar_init(bars, 1);
            asm volatile("fence.mbarrier_init.release.cluster;" ::: "memory");
            mbar_expect_tx(bars, 8192);
            tma4(sb + S_MOD1, &p.m[0], (b >> 1) * 16, (b & 1) * 256, 0, 0, bars, (POLMASK & 1) ? pol_norm : pol_first);
            TS(28);
#pragma unroll
            for (int i = 1; i < NBAR; i++) mbar_init(bars + i * 8, i == B_UK ? 8 : 1);
            asm volatile("fence.mbarrier_init.release.cluster;" ::: "memory");
            mbar_expect_tx(bars + B_X * 8, 8192); mbar_expect_tx(bars + (B_X + 1) * 8, 8192);
        }
        __syncwarp();
        TS(27);
        bar_arrive(1, NTHR - 32);
        {
            const int c = lane;
            int mi = 1, k = c - C_WQ, c0 = 0, c1 = j * 128, d1 = 32, c2 = h * 2, c3 = 0, dst = S_WQ;
            if (c >= C_WUK)  { mi = 2; k = c - C_WUK; dst = S_WUK; }
            if (c >= C_CKV)  { mi = 3; k = c - C_CKV; dst = S_CKV; c1 = pair * 128 + (k >> 2) * 64; d1 = 0; c2 = rank * 4 + (k & 3); }
            if (c == C_X)    { dst = S_XCH - 8 * 8192; c1 = pair * 128 + 64; c2 = (rank ^ 1) * 4 + 3; }
            if (c >= C_WUV)  { mi = 4; k = c - C_WUV; dst = S_WUV; c1 = j * 16; c2 = k * 2; c3 = h * 2; }
            if (c >= C_MOD2) { mi = 0; k = c - C_MOD2; dst = S_MOD2; c0 = 1024 + b * 16; c1 = 0; d1 = 256; c2 = 0; c3 = 0; }
            if (c >= C_WO)   { mi = 5; k = c - C_WO; dst = S_WO; c0 = (b & 31) * 16; c1 = (b >> 5) * 1024; }
            if (c >= C_W1)   { mi = 6; k = c - C_W1; dst = S_W1; c0 = b * 16; c1 = 0; }
            if (c >= C_W2)   { mi = 7; k = c - C_W2; dst = S_W2; c0 = 0; c1 = b * 32; d1 = 16; }
            const uint32_t wa = (uint32_t)c0 | (uint32_t)(c1 + k * d1) << 16;
            const bool keep = (POLMASK >> mi & 1) || c == C_X || c == C_X - 1;
            const uint32_t wb = (uint32_t)c2 | (uint32_t)c3 << 8 | (uint32_t)mi << 14 | (uint32_t)keep << 17 | (uint32_t)((dst >> 13) + k) << 24;
            const int nch = b < NFFN ? NCHUNK : C_W1;
#pragma unroll 1
            for (int i = 1; i < nch; i++) {
                const uint32_t ua = __shfl_sync(~0u, wa, i), ub = __shfl_sync(~0u, wb, i);
                if (i == C_X) mbar_wait(bars + B_UK * 8);
                if (i == C_W1) mbar_wait(bars + B_QK * 8);
                if (i >= WIN) mbar_wait(bars + (i - WIN) * 8);
                wait_until(t_start, p.sched[i]);
                if (lane == 0) {
                    mbar_expect_tx(bars + i * 8, 8192);
                    tma4(sb + (ub >> 24) * 8192, &p.m[(ub >> 14) & 7], ua & 0xffff, ua >> 16, ub & 0xff, (ub >> 8) & 0x3f, bars + i * 8,
                         (ub >> 17 & 1) ? pol_norm : pol_first);
                }
            }
        }
        TS(20);
        return;
    }
    if (warp == 9) {
        const int e = lane & 3;
        const float xe = __bfloat162float(p.x[b * 4 + e]), be = __bfloat162float(p.b2[b * 4 + e]);
        const uint32_t pr0 = G_PROBE + b * 32, pr4 = G_H4 + pair * 131072 + 65536 + rank * 256;
        if (lane < 4) str4(sp + pr0 + (lane & 2) * 2048 + (lane & 1) * 16, 0, 0, 0, 0);
        __syncwarp();
        uint32_t beta = 0;
                if (lane == 0) { beta = probe_near(sp, pr0, sb + S_EP + 12); sts1(sb + S_EP + 4, beta); }
        __syncwarp();
        mbar_wait_init(sb);
        if (lane == 0) mbar_arrive(bars + B_BETA * 8);
        TS(69);
        const uint32_t ep = lds1(sb + S_EP);
        const uint32_t tg = ~ep & 1u;
        beta = __shfl_sync(~0u, beta, 0);
        {
            const uint32_t prev = ldr1(sp + pr4 + 128);
            if (lane < 4) str4(sp + pr4 + (lane & 2) * 2048 + (lane & 1) * 16, 0, 0, 0, 0);
            __syncwarp();
            uint32_t w = 0;
            if (lane == 0) {
                                const uint32_t beta4 = probe_near(sp, pr4, sb + S_EP + 12);
                const uint32_t held = (prev & 24) ^ (8u << beta4);
                w = tg | beta4 << 1 | (held >> (3 + beta4) & 1) << 2 | held;
                sts1(sb + S_EP + 8, w);
                mbar_arrive(bars + B_BETA4 * 8);
            }
            w = __shfl_sync(~0u, w, 0);
            if (lane < 2) str4(sp + pr4 + 128 + lane * 16, w, w, w, w);
        }
        TS(70);
        const unsigned char* s6 = sp + pick(lane < 16 ? G_H6 + spread((lane >> 2) * 2048 + b * 16 + e * 4)
                                                      : G_MOD2 + spread((lane < 20 ? 0 : 6144) + b * 16 + e * 4), beta);
        const unsigned char* s7 = sp + pick(G_H7 + spread(lane * 2048 + b * 16), beta);
        const unsigned char* s7b = sp + pick(G_H7 + spread((lane + 32) * 2048 + b * 16), beta);
        const unsigned char* s7c = sp + pick(G_H7 + spread((lane < NFFN - 64 ? lane + 64 : lane) * 2048 + b * 16), beta);
        {
            float d0[4] = {0.f, 0.f, 0.f, 0.f}, d1[4] = {0.f, 0.f, 0.f, 0.f};
#pragma unroll 1
            for (int c = 0; c < 2; c++) {
                mbar_wait(bars + (C_MOD2 + c) * 8);
#pragma unroll 4
                for (int i = 0; i < 8; i++)
                    step32(sb + S_MOD2 + (c * 8 + i) * 1024, sb + S_SC + (c * 8 + i) * 128 + ((lane >> 2) & 1) * 64 + e * 16, lane, d0, d1);
            }
            const float r0 = (d0[0] + d0[1]) + (d1[0] + d1[1]), r1 = (d0[2] + d0[3]) + (d1[2] + d1[3]);
            const float t0 = __shfl_sync(~0u, r0, lane & 28), t1 = __shfl_sync(~0u, r1, lane & 28);
            str1(sp + G_MOD2 + spread(b * 64 + (e & 1) * 32 + (lane >> 2) * 4) + (e >> 1) * 4096, tagf((e & 1) ? t1 : t0, tg));
        }
        TS(29);
        mbar_wait(bars + B_F * 8);
        wait_until(clk32(), p.tm[D_H6]);
        uint32_t v; int it = 0;
#pragma unroll 1
        do { v = ldr1(s6); SPIN_CHECK(it); } while (__any_sync(~0u, (v ^ tg) & 1));
        const uint32_t t_6 = clk32();
        float o = lane < 16 ? u2f(v) : 0.f;
        o += __shfl_xor_sync(~0u, o, 4); o += __shfl_xor_sync(~0u, o, 8);
        const float ga = __shfl_sync(~0u, u2f(v), 16 + e), gb = __shfl_sync(~0u, u2f(v), 20 + e);
        const float x2 = fmaf(gb, be, fmaf(ga, o, xe));
        TS(21);
        wait_until(t_6, p.tm[D_H7]);
        uint4 y0, y1, y2;
#pragma unroll 1
        do {
            y0 = ldr4(s7); y1 = ldr4(s7b); y2 = ldr4(s7c);
            SPIN_CHECK(it);
        } while (__any_sync(~0u, (bad4(y0, tg) | bad4(y1, tg) | bad4(y2, tg)) & 1));
        if (lane >= NFFN - 64) y2 = make_uint4(0, 0, 0, 0);
        const float s0 = (u2f(y0.x) + u2f(y1.x)) + u2f(y2.x), s1 = (u2f(y0.y) + u2f(y1.y)) + u2f(y2.y);
        const float s2 = (u2f(y0.z) + u2f(y1.z)) + u2f(y2.z), s3 = (u2f(y0.w) + u2f(y1.w)) + u2f(y2.w);
        {
            const bool b1 = lane & 2, b0 = lane & 1;
            const float k0 = (b1 ? s2 : s0) + __shfl_xor_sync(~0u, b1 ? s0 : s2, 2), k1 = (b1 ? s3 : s1) + __shfl_xor_sync(~0u, b1 ? s1 : s3, 2);
            float k = (b0 ? k1 : k0) + __shfl_xor_sync(~0u, b0 ? k0 : k1, 1);
            k += __shfl_xor_sync(~0u, k, 4); k += __shfl_xor_sync(~0u, k, 8); k += __shfl_xor_sync(~0u, k, 16);
            if (lane < 4) p.out[b * 4 + lane] = __float2bfloat16(fmaf(gb, k, x2));
            if (b == 0 && lane == 4) str1(sp + G_EPOCH, ep + 1);
        }
        TS(22);
        return;
    }

    if (warp == 10) {
        bar_sync(1, NTHR - 32);
        const uint32_t tg = ~lds1(sb + S_EP) & 1u;
        mbar_wait(bars + B_BETA * 8);
        const uint32_t beta = lds1(sb + S_EP + 4);
        const unsigned char* sm_a = sp + pick(G_ML + spread(lane * 256 + h * 4), beta);
        const unsigned char* sm_b = sp + pick(G_ML + spread((lane + 32) * 256 + h * 4), beta);
        mbar_wait(bars + B_QK * 8);
        wait_until(clk32(), p.tm[D_ML]);
        wait_until(t_start, p.tm[T_H4] - 80);
        uint32_t ma, mb, la, lb; int it = 0;
        TS(76);
#pragma unroll 1
        do {
            ma = ldr1(sm_a); mb = ldr1(sm_b); la = ldr1(sm_a + 128); lb = ldr1(sm_b + 128);
            SPIN_CHECK(it);
        } while (__any_sync(~0u, (xo2(ma, mb, tg) | xo2(la, lb, tg)) & 1));
        TS(77);
        float M = fmaxf(u2f(ma), u2f(mb));
#pragma unroll
        for (int o = 16; o; o >>= 1) M = fmaxf(M, __shfl_xor_sync(~0u, M, o));
        const float wa = ex2(u2f(ma) - M), wb = ex2(u2f(mb) - M);
        sts1f(sb + S_ML + lane * 4, wa); sts1f(sb + S_ML + 128 + lane * 4, wb);
        __syncwarp();
        if (lane == 0) mbar_arrive(bars + B_W * 8);
        float L = wa * u2f(la) + wb * u2f(lb);
#pragma unroll
        for (int o = 16; o; o >>= 1) L += __shfl_xor_sync(~0u, L, o);
        if (lane == 0) { sts1f(sb + S_ML + 256, __fdividef(1.f, L)); mbar_arrive(bars + B_L * 8); }
        TS(78);
        return;
    }

    const int g = lane >> 2, q = lane & 3;
    const int wg = warp >> 2, wq = warp & 3;
    const uint32_t ep0 = ldr1(sp + G_EPOCH);
    const uint32_t tg = ~ep0 & 1u;
    const uint32_t cw = *reinterpret_cast<const uint32_t*>(p.c + tid * 2);
    const uint4 xa = *reinterpret_cast<const uint4*>(p.x + lane * 16), xb = *reinterpret_cast<const uint4*>(p.x + lane * 16 + 8);
    const uint32_t xw2 = *reinterpret_cast<const uint32_t*>(p.x + tid * 2);
    const float xm = __bfloat162float(p.x[j * 128 + (tid & 127)]);
    const float b1v = __bfloat162float(p.b1[(b < NFFN ? b * 16 : 0) + (lane & 15)]);
    {
        uint32_t z = ~0u, zv = tg ^ 1u;
        if (tid < 4) z = G_H1 + spread((b & 1) * 4096 + (b >> 1) * 64 + tid * 16);
        else if (tid < 8) z = G_MOD2 + spread(b * 64 + (tid & 3) * 16);
        else if (tid < 12) z = G_H6 + spread(b * 64 + (tid & 3) * 16);
        else if (tid >= 16 && tid < 32) { const uint32_t o = G_ML + spread(pair * 256 + (tid & 15) * 16) + rank * 4096; str4(sp + o, zv, zv, zv, zv); }
        else if (tid >= 32 && tid < 64) z = G_H2 + spread(b * 512 + lane * 16);
        else if (tid >= 64 && tid < 96) z = G_H5 + spread(b * 512 + lane * 16);
        else if (tid >= 96 && tid < 112) { z = G_H3 + spread((j * 2 + ((tid >> 3) & 1)) * 4096 + h * 128 + (tid & 7) * 16); zv = 0; }
        else if (tid >= 128 && b < NFFN) z = G_H7 + spread(b * 2048 + (tid - 128) * 16);
        if (z != ~0u) { str4(sp + z, zv, zv, zv, zv); str4(sp + z + 4096, zv, zv, zv, zv); }
    }
    if (tid == 0) sts1(sb + S_EP, ep0);
    sts1(sb + S_ONES + tid * 4, 0x3F803F80u);
    {
        const float c0 = bflo(cw), c1 = bfhi(cw);
        const float s0 = __fdividef(c0, 1.f + __expf(fminf(-c0, 80.f))), s1 = __fdividef(c1, 1.f + __expf(fminf(-c1, 80.f)));
        uint32_t hi, lo; split2(s0, s1, hi, lo);
        const uint32_t a = sb + S_SC + (tid >> 4) * 128 + vpos((tid & 15) * 2);
        sts1(a, hi); sts1(a + 64, lo);
    }
    TS0(0);
    bar_sync(1, NTHR - 32);
    if (warp == 7) bar_arrive(8, 64);

    const uint32_t vlane = (g & 1) * 64 + q * 16;

    {
        float d0[4] = {0.f, 0.f, 0.f, 0.f}, d1[4] = {0.f, 0.f, 0.f, 0.f};
        mbar_wait(bars + C_MOD1 * 8);
        step32(sb + S_MOD1 + warp * 1024, sb + S_SC + ((b & 1) * 8 + warp) * 128 + vlane, lane, d0, d1);
        reduce16_publish(sb, d0, d1, tid, warp, lane, sp + G_H1 + spread((b & 1) * 4096 + (b >> 1) * 64), tg);
    }
    TS0(1);
    float mean1, rstd1;
    {
        const uint32_t w[8] = {xa.x, xa.y, xa.z, xa.w, xb.x, xb.y, xb.z, xb.w};
        float s = 0.f;
#pragma unroll
        for (int i = 0; i < 8; i++) s += bflo(w[i]) + bfhi(w[i]);
#pragma unroll
        for (int o = 16; o; o >>= 1) s += __shfl_xor_sync(~0u, s, o);
        mean1 = s * (1.f / 512.f);
        float v = 0.f;
#pragma unroll
        for (int i = 0; i < 8; i++) { float a = bflo(w[i]) - mean1, c = bfhi(w[i]) - mean1; v += a * a + c * c; }
#pragma unroll
        for (int o = 16; o; o >>= 1) v += __shfl_xor_sync(~0u, v, o);
        rstd1 = rsqrtf(v * (1.f / 512.f) + 1e-5f);
    }
    if (tid < 128) {
        const unsigned char* s0 = sp + G_H1 + j * 512 + tid * 4;
        const unsigned char* s1 = s0 + 8192;
        uint4 a; int it = 0;
        wait_until(t_start, p.tm[T_H1]);
#pragma unroll 1
        do {
            a.x = ldr1(s0); a.y = ldr1(s1); a.z = ldr1(s0 + 2048); a.w = ldr1(s1 + 2048);
            SPIN_CHECK(it);
        } while (bad4(a, tg) & 1);
        const float hv = (xm - mean1) * rstd1 * (1.f + (u2f(a.z) + u2f(a.w))) + (u2f(a.x) + u2f(a.y));
        uint32_t hi, lo; split2(hv, 0.f, hi, lo);
        const uint32_t ad = sb + S_VEC + (tid >> 5) * 128 + vpos(tid & 31);
        stsh(ad, hi); stsh(ad + 64, lo);
    }
    TS0(2);
    bar_sync(2, 256);
    {
        float r0, r1;
        gemv128<true>(sb + S_WQ, sb + S_VEC, bars + C_WQ * 8, warp, lane, r0, r1);
        const float t0 = __shfl_sync(~0u, r0, lane & 28), t1 = __shfl_sync(~0u, r1, lane & 28);
        str1(sp + G_H2 + spread(b * 512 + warp * 64 + (q & 1) * 32 + g * 4) + (q >> 1) * 4096, tagf((q & 1) ? t1 : t0, tg));
    }
    TS0(3);
    mbar_wait(bars + B_BETA * 8);
    const uint32_t beta = lds1(sb + S_EP + 4);
    bar_sync(2, 256);
    if (tid < 128) {
        const unsigned char* src = sp + pick(G_H2 + spread(h * 2048 + tid * 4), beta);
        uint4 a; int it = 0;
#pragma unroll 1
        do {
            a.x = ldr1(src); a.y = ldr1(src + 512); a.z = ldr1(src + 1024); a.w = ldr1(src + 1536);
            SPIN_CHECK(it);
        } while (bad4(a, tg) & 1);
        const float qv = ((u2f(a.x) + u2f(a.y)) + (u2f(a.z) + u2f(a.w))) * (0.08838834764831845f * 1.4426950408889634f);
        uint32_t hi, lo; split2(qv, 0.f, hi, lo);
        const uint32_t ad = sb + S_VEC + (tid >> 5) * 128 + vpos(tid & 31);
        stsh(ad, hi); stsh(ad + 64, lo);
    }
    TS0(4);
    bar_sync(2, 256);
    {
        float r0, r1;
        gemv128<false>(sb + S_WUK, sb + S_VEC, bars + C_WUK * 8, warp, lane, r0, r1);
        const float n0 = __shfl_down_sync(~0u, r0, 4), m0 = __shfl_up_sync(~0u, r1, 4);
        const uint32_t w = (g & 1) ? packbf(m0, r1) : packbf(r0, n0);
        const uint32_t w2 = __shfl_sync(~0u, w, lane & 28);
        if (q < 2) {
            const int chunk = ((warp & 3) * 2 + (g & 1)) ^ (h & 7);
            str1(sp + G_H3 + (j * 2 + (warp >> 2)) * 8192 + q * 4096 + h * 128 + chunk * 16 + (g >> 1) * 4, w2 ^ 0xFFFF0000u);
        }
        if (lane == 0) mbar_arrive(bars + B_UK * 8);
    }
    TS0(5);
    {
        const unsigned char* src[5];
#pragma unroll
        for (int i = 0; i < 5; i++) src[i] = sp + pick(G_H3 + (i < 4 ? rank * 4 + i : (rank ^ 1) * 4 + 3) * 8192 + tid * 16, beta);
        uint4 v[5];
        wait_until(t_start, p.tm[T_H3]);
#pragma unroll
        for (int i = 0; i < 5; i++) v[i] = ldr4(src[i]);
        int it = 0;
#pragma unroll 1
        while (true) {
            bool ok = true;
#pragma unroll
            for (int i = 0; i < 5; i++) if (!nz4(v[i])) { v[i] = ldr4(src[i]); ok = false; }
            if (__all_sync(~0u, ok)) break;
            SPIN_CHECK(it);
        }
        TS0(31);
#pragma unroll
        for (int i = 0; i < 5; i++)
            sts4(sb + S_QABS + i * 4096 + tid * 16, v[i].x ^ 0xFFFF0000u, v[i].y ^ 0xFFFF0000u, v[i].z ^ 0xFFFF0000u, v[i].w ^ 0xFFFF0000u);
        fence_async();
        bar_sync(2, 256);
    }
    TS0(6);
    if (wg) {
        uint32_t bw; int it = 0;
#pragma unroll 1
        do { bw = ldr1(sp + G_H4 + 65536 + 128 + ((tid & 127) >> 1) * 131072 + (tid & 1) * 256); SPIN_CHECK(it); } while (__any_sync(~0u, (bw ^ tg) & 1));
        const uint32_t mb = __ballot_sync(~0u, bw & 2), mt = __ballot_sync(~0u, bw & 4);
        if (lane == 0) sts2(sb + S_B4 + wq * 8, mb, mt);
    }
    mbar_wait(bars + B_BETA4 * 8);
    const uint32_t rec = lds1(sb + S_EP + 8), tg4w = rec >> 2 & 1;
    unsigned char* const h4dst = sp + pick(G_H4 + pair * 131072 + spread(q * 2048 + wq * 256 + rank * 128 + g * 8), rec >> 1);
    {
        float s[16];
#pragma unroll
        for (int i = 0; i < 16; i++) s[i] = 0.f;
        const uint32_t xo = (wg ? S_XBUF1 : S_XBUF0) + (tid & 127) * 16;
#pragma unroll 1
        for (int cg = 0; cg < 4 - wg; cg++) {
            mbar_wait(bars + (C_CKV + wg * 4 + cg) * 8);
            const uint64_t da = mkdesc(sb + S_CKV + (wg * 4 + cg) * 8192), db = mkdesc(sb + S_QABS + cg * 4096);
            wg_fence();
#pragma unroll
            for (int k = 0; k < 4; k++) wgmma_n32<0>(s, da + k * 2, db + k * 2, 1);
            wg_commit();
        }
        wg_wait<0>();
        reg_fence16(s);
        TS0(64);
        {
            uint32_t ra, rb;
            asm("mapa.shared::cluster.u32 %0, %1, %2;" : "=r"(ra) : "r"(sb + xo), "r"(rank ^ 1));
            asm("mapa.shared::cluster.u32 %0, %1, %2;" : "=r"(rb) : "r"(bars + (B_X + wg) * 8), "r"(rank ^ 1));
#pragma unroll
            for (int i = 0; i < 4; i++)
                asm volatile("st.async.weak.shared::cluster.mbarrier::complete_tx::bytes.v4.f32 [%0], {%1,%2,%3,%4}, [%5];"
                             ::"r"(ra + i * 2048), "f"(s[4 * i]), "f"(s[4 * i + 1]), "f"(s[4 * i + 2]), "f"(s[4 * i + 3]), "r"(rb) : "memory");
        }
        if (wg) {
#pragma unroll 1
            for (int c = 0; c < 2; c++) {
                mbar_wait(bars + (C_X - 1 + c) * 8);
                const uint64_t da = mkdesc(sb + (c ? S_XCH : S_CKV + 7 * 8192)), db = mkdesc(sb + S_QABS + (3 + c) * 4096);
                wg_fence();
#pragma unroll
                for (int k = 0; k < 4; k++) wgmma_n32<0>(s, da + k * 2, db + k * 2, 1);
                wg_commit();
            }
        }
        mbar_wait_cluster(bars + (B_X + wg) * 8);
        float4 xs[4];
#pragma unroll
        for (int i = 0; i < 4; i++) xs[i] = lds4f(sb + xo + i * 2048);
        wg_wait<0>();
        reg_fence16(s);
        TS4(7); TS0(65);
#pragma unroll
        for (int i = 0; i < 4; i++) { s[4 * i] += xs[i].x; s[4 * i + 1] += xs[i].y; s[4 * i + 2] += xs[i].z; s[4 * i + 3] += xs[i].w; }
        const bool b2 = lane & 16, b1 = lane & 8, b0 = lane & 4;
        const uint32_t hoff = (8 * (g >> 1) + 2 * q + (g & 1)) * 32 + warp * 4;
        {
            float v[8];
#pragma unroll
            for (int i = 0; i < 4; i++) { v[2 * i] = fmaxf(s[4 * i], s[4 * i + 2]); v[2 * i + 1] = fmaxf(s[4 * i + 1], s[4 * i + 3]); }
            float u[4];
#pragma unroll
            for (int k = 0; k < 4; k++) u[k] = fmaxf(b2 ? v[k + 4] : v[k], __shfl_xor_sync(~0u, b2 ? v[k] : v[k + 4], 16));
            float t[2];
#pragma unroll
            for (int k = 0; k < 2; k++) t[k] = fmaxf(b1 ? u[k + 2] : u[k], __shfl_xor_sync(~0u, b1 ? u[k] : u[k + 2], 8));
            sts1f(sb + S_MAX + hoff, fmaxf(b0 ? t[1] : t[0], __shfl_xor_sync(~0u, b0 ? t[0] : t[1], 4)));
        }
        if (wg == 0) { bar_arrive(4, 256); bar_sync(3, 128); } else { bar_arrive(7, 256); bar_sync(4, 256); }
        TS4(66);
        float mh;
        {
            const float4 ma = lds4f(sb + S_MAX + lane * 32), mb = lds4f(sb + S_MAX + lane * 32 + wg * 16);
            mh = fmaxf(fmaxf(fmaxf(ma.x, ma.y), fmaxf(ma.z, ma.w)), fmaxf(fmaxf(mb.x, mb.y), fmaxf(mb.z, mb.w)));
        }
        if (warp == 4 + rank) {
            str1(sp + G_ML + spread(pair * 256 + lane * 4) + rank * 4096, tagf(mh, tg));
            if (lane == 0) mbar_arrive(bars + B_QK * 8);
        }
        uint32_t pk[8];
#pragma unroll
        for (int i = 0; i < 4; i++) {
            const float m0 = __shfl_sync(~0u, mh, 8 * i + 2 * q), m1 = __shfl_sync(~0u, mh, 8 * i + 2 * q + 1);
            const float p0 = ex2(s[4 * i] - m0), p1 = ex2(s[4 * i + 1] - m1), p2 = ex2(s[4 * i + 2] - m0), p3 = ex2(s[4 * i + 3] - m1);
            pk[2 * i] = packbf(p0, p1); pk[2 * i + 1] = packbf(p2, p3);
        }
        {
            const int t = lane >> 3, r8 = lane & 7;
            const uint32_t a = sb + S_P + wg * 4096 + ((t >> 1) * 8 + r8) * 128 + (((2 * wq + (t & 1)) ^ r8) << 4);
            stsm4t(a, pk[0], pk[1], pk[2], pk[3]);
            stsm4t(a + 2048, pk[4], pk[5], pk[6], pk[7]);
        }
        fence_async();
        TS4(67); TS0(68);
        if (wg) {
            bar_arrive(5, 256);
        } else {
            float o0[16], o1[16], o2[16], o3[16], ol[16];
            const uint64_t d1 = mkdesc(sb + S_ONES) & ~(0x3FFFull << 32);
            const uint64_t db = mkdesc(sb + S_P), da = mkdesc(sb + S_CKV);
            bar_sync(3, 128);
            wg_fence();
#pragma unroll
            for (int k = 0; k < 4; k++) {
                wgmma_n32<1>(o0, da + k * 128, db + k * 2, k);
                wgmma_n32<1>(o1, da + 512 + k * 128, db + k * 2, k);
                wgmma_n32<1>(o2, da + 1024 + k * 128, db + k * 2, k);
                wgmma_n32<1>(o3, da + 1536 + k * 128, db + k * 2, k);
                wgmma_n32<0>(ol, d1, db + k * 2, k);
            }
            wg_commit();
            wg_wait<0>();
            reg_fence16(o0); reg_fence16(o1); reg_fence16(o2); reg_fence16(o3); reg_fence16(ol);
            TS0(23);
            bar_sync(7, 256);
            {
                const float4 mb = lds4f(sb + S_MAX + lane * 32 + 16);
                const float al = ex2(mh - fmaxf(mh, fmaxf(fmaxf(mb.x, mb.y), fmaxf(mb.z, mb.w))));
#pragma unroll
                for (int i = 0; i < 4; i++) {
                    const float a0 = __shfl_sync(~0u, al, 8 * i + 2 * q), a1 = __shfl_sync(~0u, al, 8 * i + 2 * q + 1);
                    o0[4 * i] *= a0; o0[4 * i + 1] *= a1; o0[4 * i + 2] *= a0; o0[4 * i + 3] *= a1;
                    o1[4 * i] *= a0; o1[4 * i + 1] *= a1; o1[4 * i + 2] *= a0; o1[4 * i + 3] *= a1;
                    o2[4 * i] *= a0; o2[4 * i + 1] *= a1; o2[4 * i + 2] *= a0; o2[4 * i + 3] *= a1;
                    o3[4 * i] *= a0; o3[4 * i + 1] *= a1; o3[4 * i + 2] *= a0; o3[4 * i + 3] *= a1;
                    ol[4 * i] *= a0; ol[4 * i + 1] *= a1; ol[4 * i + 2] *= a0; ol[4 * i + 3] *= a1;
                }
            }
            bar_sync(5, 256);
            wg_fence();
#pragma unroll
            for (int k = 0; k < 4; k++) wgmma_n32<0>(ol, d1, db + 256 + k * 2, 1);
            wg_commit();
#pragma unroll
            for (int k = 0; k < 4; k++) {
                wgmma_n32<1>(o0, da + 2048 + k * 128, db + 256 + k * 2, 1);
                wgmma_n32<1>(o1, da + 2048 + 512 + k * 128, db + 256 + k * 2, 1);
            }
            wg_commit();
#pragma unroll
            for (int k = 0; k < 4; k++) {
                wgmma_n32<1>(o2, da + 2048 + 1024 + k * 128, db + 256 + k * 2, 1);
                wgmma_n32<1>(o3, da + 2048 + 1536 + k * 128, db + 256 + k * 2, 1);
            }
            wg_commit();
#define O_STORE(A, B, OFF) _Pragma("unroll") for (int i = 0; i < 4; i++) _Pragma("unroll") for (int e = 0; e < 2; e++) { \
                const float f0 = u2f((__float_as_uint(A[4 * i + e]) + 0x10000u) & 0xFFFE0000u); \
                str64(h4dst + (OFF) + i * 16384 + e * 1024, packbf(f0, A[4 * i + 2 + e]) | tg4w, packbf(B[4 * i + e], B[4 * i + 2 + e])); }
            wg_wait<2>();
            reg_fence16(ol);
            if (warp == 0) {
                const float lv = (g & 4) ? ((g & 2) ? ((g & 1) ? ol[13] : ol[12]) : ((g & 1) ? ol[9] : ol[8]))
                                         : ((g & 2) ? ((g & 1) ? ol[5] : ol[4]) : ((g & 1) ? ol[1] : ol[0]));
                str1(sp + G_ML + spread(pair * 256 + 128 + (8 * (g >> 1) + 2 * q + (g & 1)) * 4) + rank * 4096, tagf(lv, tg));
            }
            __syncwarp();
            TS0(8);
            wg_wait<1>();
            reg_fence16(o0); reg_fence16(o1);
            TS0(24);
            O_STORE(o0, o1, 0);
            __syncwarp();
            wg_wait<0>();
            reg_fence16(o2); reg_fence16(o3);
            O_STORE(o2, o3, 64);
        }
    }
    TS0(9);
    const uint32_t t_o = clk32();
    uint32_t af[8][4];
    {
        const int sg = tid >> 4, u = tid & 15;
        uint32_t a0;
        {
            const int m = lane >> 3, r8 = lane & 7;
            const int row = (m >> 1) * 16 + (r8 >> 1) * 2 + (r8 & 1) * 8;
            a0 = sb + S_WUV + wg * 4096 + row * 128 + (((wq * 2 + (m & 1)) ^ (row & 7)) << 4);
        }
        const unsigned char* src[4];
        uint32_t tg4[4];
#pragma unroll
        for (int i = 0; i < 4; i++) {
            const float2 m = lds2f(sb + S_B4 + i * 8);
            src[i] = sp + pick(G_H4 + (sg + 16 * i) * 131072 + spread(b * 256 + u * 16), __float_as_uint(m.x) >> (sg * 2 + (u >> 3)));
            tg4[i] = __float_as_uint(m.y) >> (sg * 2 + (u >> 3));
        }
        uint4 v[4];
        uint32_t have = 0;
        int it = 0;
        wait_until(t_o, p.tm[D_H4]);
        wait_until(t_start, p.tm[T_H4]);
#pragma unroll
        for (int i = 0; i < 4; i++) v[i] = ldr64x2(src[i]);
        TS0(10);
        float wt[4];
        bool first = true;
#pragma unroll 1
        while (true) {
            const uint32_t now = mbar_mask4(bars + C_WUV * 8) & ~have;
#pragma unroll
            for (int i = 0; i < 4; i++)
                if (now >> i & 1) { ldsm4t(a0 + i * 8192, af[2 * i]); ldsm4t((a0 + i * 8192 + 128) ^ 16, af[2 * i + 1]); }
            have |= now;
            if (first) {
                mbar_wait(bars + B_W * 8);
#pragma unroll
                for (int i = 0; i < 4; i++) wt[i] = lds1f(sb + S_ML + (sg + 16 * i) * 4);
                first = false;
            }
            bool ok = true;
#pragma unroll
            for (int i = 0; i < 4; i++) if (xo2(v[i].x, v[i].z, tg4[i]) & 1) { v[i] = ldr64x2(src[i]); ok = false; }
            if (__all_sync(~0u, ok)) break;
            SPIN_CHECK(it);
        }
        float acc[8] = {0.f, 0.f, 0.f, 0.f, 0.f, 0.f, 0.f, 0.f};
#pragma unroll
        for (int i = 0; i < 4; i++) {
            const uint32_t w[4] = {v[i].x & ~1u, v[i].y, v[i].z & ~1u, v[i].w};
#pragma unroll
            for (int k = 0; k < 4; k++) {
                acc[2 * k] = fmaf(wt[i], bflo(w[k]), acc[2 * k]);
                acc[2 * k + 1] = fmaf(wt[i], bfhi(w[k]), acc[2 * k + 1]);
            }
        }
        TS0(25);
        {
            const bool up = lane & 16;
            float r[4];
#pragma unroll
            for (int k = 0; k < 4; k++) r[k] = ((up ? acc[k + 4] : acc[k]) + __shfl_xor_sync(~0u, up ? acc[k] : acc[k + 4], 16));
            sts2(sb + S_RED + warp * 320 + u * 16 + (up ? 8 : 0), packbf(r[0], r[1]), packbf(r[2], r[3]));
        }
        bar_sync(2, 256);
        uint4 bq[4];
#pragma unroll
        for (int i = 0; i < 4; i++) bq[i] = lds4(sb + S_RED + g * 320 + i * 64 + q * 16);
#pragma unroll
        for (int i = 0; i < 4; i++)
            if (!(have >> i & 1)) {
                mbar_wait(bars + (C_WUV + i) * 8);
                ldsm4t(a0 + i * 8192, af[2 * i]); ldsm4t((a0 + i * 8192 + 128) ^ 16, af[2 * i + 1]);
            }
        float d[4][4];
#pragma unroll
        for (int i = 0; i < 4; i++) {
            d[i][0] = d[i][1] = d[i][2] = d[i][3] = 0.f;
            mma16816(d[i], af[2 * i], bq[i].x, bq[i].y);
            mma16816(d[i], af[2 * i + 1], bq[i].z, bq[i].w);
        }
        mbar_wait(bars + B_L * 8);
        const float rl = lds1f(sb + S_ML + 256);
        const float r0 = ((d[0][0] + d[0][1]) + (d[1][0] + d[1][1])) + ((d[2][0] + d[2][1]) + (d[3][0] + d[3][1]));
        const float r1 = ((d[0][2] + d[0][3]) + (d[1][2] + d[1][3])) + ((d[2][2] + d[2][3]) + (d[3][2] + d[3][3]));
        float r = ((q & 1) ? r1 : r0) + __shfl_xor_sync(~0u, (q & 1) ? r0 : r1, 1);
        r += __shfl_xor_sync(~0u, r, 2);
        str1(sp + G_H5 + spread(b * 512 + warp * 64 + (q & 1) * 32 + g * 4) + (q >> 1) * 4096, tagf(r * rl, tg));
        if (tid >= 224) str4(sp + G_H3 + (j * 2 + ((tid >> 3) & 1)) * 8192 + (tid & 16) * 256 + h * 128 + (tid & 7) * 16, 0, 0, 0, 0);
    }
    const uint32_t t_e = clk32();
    TS0(12);
    uint2 m0, m1, m2;
    const unsigned char* const sm0 = sp + pick(G_MOD2 + tid * 8, beta);
    const unsigned char* const sm2 = sp + pick(G_MOD2 + 8192 + tid * 8, beta);
    {
        const int m = lane >> 3, r8 = lane & 7;
        const uint32_t a0 = sb + S_WO + warp * 1024 + ((m >> 1) * 8 + r8) * 32 + (((m & 1) ^ (r8 >> 2)) << 4);
        const unsigned char* src = sp + pick(G_H5 + spread(((b >> 5) * 8 + warp) * 2048 + lane * 16), beta);
        uint4 a0_, a1, a2, a3; int it = 0;
        uint32_t have = 0;
        wait_until(t_e, p.tm[D_H5]);
        a0_ = ldr4(src); a1 = ldr4(src + 512); a2 = ldr4(src + 1024); a3 = ldr4(src + 1536);
#pragma unroll 1
        while (true) {
            const uint32_t now = mbar_mask4(bars + C_WO * 8) & ~have;
#pragma unroll
            for (int i = 0; i < 4; i++)
                if (now >> i & 1) { ldsm4t(a0 + i * 8192, af[2 * i]); ldsm4t(a0 + i * 8192 + 512, af[2 * i + 1]); }
            have |= now;
            bool ok = true;
            if (bad4(a0_, tg) & 1) { a0_ = ldr4(src); ok = false; }
            if (bad4(a1, tg) & 1) { a1 = ldr4(src + 512); ok = false; }
            if (bad4(a2, tg) & 1) { a2 = ldr4(src + 1024); ok = false; }
            if (bad4(a3, tg) & 1) { a3 = ldr4(src + 1536); ok = false; }
            if (__all_sync(~0u, ok)) break;
            SPIN_CHECK(it);
        }
        const float v0 = (u2f(a0_.x) + u2f(a1.x)) + (u2f(a2.x) + u2f(a3.x)), v1 = (u2f(a0_.y) + u2f(a1.y)) + (u2f(a2.y) + u2f(a3.y));
        const float v2 = (u2f(a0_.z) + u2f(a1.z)) + (u2f(a2.z) + u2f(a3.z)), v3 = (u2f(a0_.w) + u2f(a1.w)) + (u2f(a2.w) + u2f(a3.w));
        uint32_t hi, lo;
        const uint32_t a = sb + S_FVEC + (tid >> 3) * 128 + vpos((tid & 7) * 4);
        split2(v0, v1, hi, lo); sts1(a, hi); sts1(a + 64, lo);
        split2(v2, v3, hi, lo); sts1(a + 16, hi); sts1(a + 16 + 64, lo);
        TS0(14);
        bar_sync(2, 256);
        m0 = ldr2(sm0); m1 = ldr2(sm0 + 2048); m2 = ldr2(sm2);
        uint4 bq[4];
#pragma unroll
        for (int i = 0; i < 4; i++) bq[i] = lds4(sb + S_FVEC + (i * 8 + warp) * 128 + vlane);
#pragma unroll
        for (int i = 0; i < 4; i++)
            if (!(have >> i & 1)) {
                mbar_wait(bars + (C_WO + i) * 8);
                ldsm4t(a0 + i * 8192, af[2 * i]); ldsm4t(a0 + i * 8192 + 512, af[2 * i + 1]);
            }
        float d[4][4];
#pragma unroll
        for (int i = 0; i < 4; i++) {
            d[i][0] = d[i][1] = d[i][2] = d[i][3] = 0.f;
            mma16816(d[i], af[2 * i], bq[i].x, bq[i].y);
            mma16816(d[i], af[2 * i + 1], bq[i].z, bq[i].w);
        }
#pragma unroll
        for (int e = 0; e < 4; e++) { d[0][e] += d[1][e]; d[2][e] += d[3][e]; }
        TS0(15);
        reduce16_publish(sb, d[0], d[2], tid, warp, lane, sp + G_H6 + spread(b * 64), tg);
        if (tid == 32) mbar_arrive(bars + B_F * 8);
    }
    const uint32_t t_f = clk32();
    TS0(26);
    if (b < NFFN) {
        const uint32_t ga_ = sb + S_GVEC + (warp * 2 + (lane >> 4)) * 512 + vpos((lane & 15) * 2);
        {
            int it = 0;
#pragma unroll 1
            while ((bad2(m0, tg) | bad2(m1, tg) | bad2(m2, tg)) & 1) {
                m0 = ldr2(sm0); m1 = ldr2(sm0 + 2048); m2 = ldr2(sm2);
                SPIN_CHECK(it);
            }
        }
        const float ga0 = u2f(m0.x), ga1 = u2f(m0.y), g0 = 1.f + u2f(m2.x), g1 = 1.f + u2f(m2.y);
        {
            uint32_t hi, lo;
            split2(g0, g1, hi, lo); sts1(ga_ + 128, hi); sts1(ga_ + 192, lo);
            split2(u2f(m1.x), u2f(m1.y), hi, lo); sts1(ga_ + 256, hi); sts1(ga_ + 320, lo);
        }
        TS0(16);
        const int m = lane >> 3, r8 = lane & 7;
        const uint32_t a0 = sb + S_W1 + warp * 2048 + ((m >> 1) * 8 + r8) * 32 + (((m & 1) ^ (r8 >> 2)) << 4);
        uint32_t w2r[16];
        uint32_t have = 0;
#define LOAD_FFN(now) do { \
            if ((now) >> wg & 1) { _Pragma("unroll") for (int i = 0; i < 4; i++) ldsm4t(a0 + i * 512, af[i]); } \
            if ((now) & 4) { _Pragma("unroll") for (int r = 0; r < 8; r++) w2r[r] = lds1(sb + S_W2 + r * 1024 + tid * 4); } \
            if ((now) & 8) { _Pragma("unroll") for (int r = 8; r < 16; r++) w2r[r] = lds1(sb + S_W2 + r * 1024 + tid * 4); } } while (0)
        float x20, x21;
        {
            const unsigned char* s0 = sp + pick(G_H6 + tid * 8, beta);
            const unsigned char* s2 = sp + pick(G_H6 + 8192 + tid * 8, beta);
            uint2 c0, c1, c2, c3; int it = 0;
            wait_until(t_f, p.tm[D_H6]);
#pragma unroll 1
            do {
                c0 = ldr2(s0); c1 = ldr2(s0 + 2048); c2 = ldr2(s2); c3 = ldr2(s2 + 2048);
                const uint32_t now = mbar_mask4(bars + C_W1 * 8) & ~have;
                LOAD_FFN(now);
                have |= now;
                SPIN_CHECK(it);
            } while (__any_sync(~0u, (bad2(c0, tg) | bad2(c1, tg) | bad2(c2, tg) | bad2(c3, tg)) & 1));
            x20 = bflo(xw2) + ga0 * ((u2f(c0.x) + u2f(c1.x)) + (u2f(c2.x) + u2f(c3.x)));
            x21 = bfhi(xw2) + ga1 * ((u2f(c0.y) + u2f(c1.y)) + (u2f(c2.y) + u2f(c3.y)));
            uint32_t hi, lo;
            split2(x20 * g0, x21 * g1, hi, lo); sts1(ga_, hi); sts1(ga_ + 64, lo);
            split2(x20, x21, hi, lo); sts1(ga_ + 384, hi); sts1(ga_ + 448, lo);
        }
        TS0(17);
        __syncwarp();
        const uint32_t va = sb + S_GVEC + warp * 1024 + g * 64 + q * 16;
        const uint4 bq0 = lds4(va), bq1 = lds4(va + 512);
        if (!(have >> wg & 1)) {
            mbar_wait(bars + (C_W1 + wg) * 8);
#pragma unroll
            for (int i = 0; i < 4; i++) ldsm4t(a0 + i * 512, af[i]);
        }
        float d0[4] = {0.f, 0.f, 0.f, 0.f}, d1[4] = {0.f, 0.f, 0.f, 0.f}, d2[4] = {0.f, 0.f, 0.f, 0.f}, d3[4] = {0.f, 0.f, 0.f, 0.f};
        mma16816(d0, af[0], bq0.x, bq0.y); mma16816(d1, af[1], bq0.z, bq0.w);
        mma16816(d2, af[2], bq1.x, bq1.y); mma16816(d3, af[3], bq1.z, bq1.w);
        float e0[4] = {0.f, 0.f, 0.f, 0.f}, e1[4] = {0.f, 0.f, 0.f, 0.f};
        {
            const uint32_t one = 0x3F803F80u;
            const uint32_t t0[4] = {bq0.x, one, bq0.y, one}, t1[4] = {bq0.z, one, bq0.w, one};
            const uint32_t t2[4] = {bq1.x, one, bq1.y, one}, t3[4] = {bq1.z, one, bq1.w, one};
            mma16816(e0, t0, bq0.x, bq0.y); mma16816(e1, t1, bq0.z, bq0.w);
            mma16816(e0, t2, bq1.x, bq1.y); mma16816(e1, t3, bq1.z, bq1.w);
        }
        {
            const bool st = q == 3;
            const float lo_ = st ? (e0[0] + e0[1]) + (e1[0] + e1[1]) : ((d0[0] + d0[1]) + (d1[0] + d1[1])) + ((d2[0] + d2[1]) + (d3[0] + d3[1]));
            const float hi_ = st ? (e0[2] + e0[3]) + (e1[2] + e1[3]) : ((d0[2] + d0[3]) + (d1[2] + d1[3])) + ((d2[2] + d2[3]) + (d3[2] + d3[3]));
            sts1f(sb + S_RED + q * 512 + g * 32 + warp * 4, lo_);
            sts1f(sb + S_RED + q * 512 + (g + 8) * 32 + warp * 4, hi_);
        }
        if ((have & 12) != 12) {
            mbar_wait(bars + C_W2 * 8); mbar_wait(bars + (C_W2 + 1) * 8);
#pragma unroll
            for (int r = 0; r < 16; r++) w2r[r] = lds1(sb + S_W2 + r * 1024 + tid * 4);
        }
        float w2f[32];
#pragma unroll
        for (int r = 0; r < 16; r++) { w2f[2 * r] = bflo(w2r[r]); w2f[2 * r + 1] = bfhi(w2r[r]); }
        if (warp) {
#pragma unroll
            for (int r = 0; r < 32; r++) asm volatile("" : "+f"(w2f[r]));
        }
        TS0(18);
        bar_sync(2, 256);
        if (warp == 0) {
            const uint32_t a = sb + S_RED + (lane & 15) * 32 + (lane >> 4) * 16;
            const uint32_t as = sb + S_RED + 1536 + (lane >> 4) * 16;
            const float4 sa = lds4f(as + 8 * 32), ta = lds4f(as + 6 * 32), tc = lds4f(as + 7 * 32);
            const float4 U = lds4f(a), G = lds4f(a + 512), S = lds4f(a + 1024);
            float mu = (sa.x + sa.y) + (sa.z + sa.w), ex = ((ta.x + ta.y) + (ta.z + ta.w)) + ((tc.x + tc.y) + (tc.z + tc.w));
            float us = (U.x + U.y) + (U.z + U.w), gs = (G.x + G.y) + (G.z + G.w), ss = (S.x + S.y) + (S.z + S.w);
            mu += __shfl_xor_sync(~0u, mu, 16); ex += __shfl_xor_sync(~0u, ex, 16);
            us += __shfl_xor_sync(~0u, us, 16); gs += __shfl_xor_sync(~0u, gs, 16); ss += __shfl_xor_sync(~0u, ss, 16);
            mu *= 1.f / 512.f;
            float rstd;
            asm("rsqrt.approx.ftz.f32 %0, %1;" : "=f"(rstd) : "f"(fmaxf(fmaf(ex, 1.f / 512.f, -mu * mu), 0.f) + 1e-5f));
            const float pre = (us - mu * gs) * rstd + (ss + b1v);
            const float z = pre * fmaf(pre * pre, 0.044715f * 2.302208198f, 2.302208198f);
            sts1f(sb + S_STAT + (lane & 15) * 4, __fdividef(pre, 1.f + ex2(fminf(-z, 126.f))));
        }
        bar_sync(2, 256);
        float y0a = 0.f, y0b = 0.f, y1a = 0.f, y1b = 0.f;
#pragma unroll
        for (int r = 0; r < 16; r += 4) {
            const float4 f = lds4f(sb + S_STAT + r * 4);
            y0a = fmaf(f.x, w2f[2 * r], y0a); y1a = fmaf(f.x, w2f[2 * r + 1], y1a);
            y0b = fmaf(f.y, w2f[2 * r + 2], y0b); y1b = fmaf(f.y, w2f[2 * r + 3], y1b);
            y0a = fmaf(f.z, w2f[2 * r + 4], y0a); y1a = fmaf(f.z, w2f[2 * r + 5], y1a);
            y0b = fmaf(f.w, w2f[2 * r + 6], y0b); y1b = fmaf(f.w, w2f[2 * r + 7], y1b);
        }
        unsigned char* d7 = sp + G_H7 + spread(b * 2048 + tid * 8);
        const uint32_t w0 = tagf(y0a + y0b, tg), w1 = tagf(y1a + y1b, tg);
        str2(d7, w0, w1); str2(d7 + 4096, w0, w1);
        TS0(19);
    }
}

typedef CUresult (*EncodeFn)(CUtensorMap*, CUtensorMapDataType, cuuint32_t, void*, const cuuint64_t*, const cuuint64_t*,
                             const cuuint32_t*, const cuuint32_t*, CUtensorMapInterleave, CUtensorMapSwizzle,
                             CUtensorMapL2promotion, CUtensorMapFloatOOBfill);

CUtensorMapL2promotion g_prom_narrow = CU_TENSOR_MAP_L2_PROMOTION_L2_128B;
void make_map(EncodeFn enc, CUtensorMap* m, const void* ptr, uint64_t d0, uint64_t d1, uint64_t d2, uint64_t d3,
              uint64_t s1, uint64_t s2, uint64_t s3, uint32_t b0, uint32_t b1, uint32_t b2, uint32_t b3, CUtensorMapSwizzle sw) {
    const auto prom = b0 == 16 ? g_prom_narrow : CU_TENSOR_MAP_L2_PROMOTION_L2_128B;
    cuuint64_t dims[4] = {d0, d1, d2, d3};
    cuuint64_t st[3] = {s1, s2, s3};
    cuuint32_t box[4] = {b0, b1, b2, b3};
    cuuint32_t es[4] = {1, 1, 1, 1};
    enc(m, CU_TENSOR_MAP_DATA_TYPE_BFLOAT16, 4, const_cast<void*>(ptr), dims, st, box, es, CU_TENSOR_MAP_INTERLEAVE_NONE, sw,
        prom, CU_TENSOR_MAP_FLOAT_OOB_FILL_NONE);
}

uint16_t g_tm[NTM] = {3400, 6680, 14740, 800, 370, 1120, 520, 300};
uint16_t g_sched[32] = {0,1120,1708,2296,2884,3472,4060,4648,5236,5824,6412,7000,7588,8176,8764,9352,
                        9940,10040,10410,10630,11590,12710,15020,15710,16130,16420,17430,18140,18780,19880,20330,20610};

}

extern "C" void kernel_launch(void* const* d_in, const int* in_sizes, int n_in, void* d_out, int out_size) {
    (void)in_sizes; (void)n_in; (void)out_size;
    static EncodeFn enc = nullptr;
    static unsigned char* scratch = nullptr;
    if (!enc) {
        cudaGetSymbolAddress((void**)&scratch, g_scratch);
        scratch = (unsigned char*)(((uintptr_t)scratch + (2 << 20) - 1) & ~(uintptr_t)((2 << 20) - 1));
        void* fn = nullptr;
        cudaDriverEntryPointQueryResult qr;
        cudaGetDriverEntryPoint("cuTensorMapEncodeTiled", &fn, cudaEnableDefault, &qr);
        enc = (EncodeFn)fn;
        cudaFuncSetAttribute(fused_decode_kernel, cudaFuncAttributeMaxDynamicSharedMemorySize, SMEM_BYTES);
    }
    Params p;
    const auto S128 = CU_TENSOR_MAP_SWIZZLE_128B, S32 = CU_TENSOR_MAP_SWIZZLE_32B, S0 = CU_TENSOR_MAP_SWIZZLE_NONE;
    make_map(enc, &p.m[0], d_in[12], 3072, 512, 1, 1, 6144, 6144 * 512, 6144 * 512, 16, 256, 1, 1, S32);
    make_map(enc, &p.m[1], d_in[2], 64, 512, 64, 1, 8192, 128, 8192 * 512, 64, 32, 2, 1, S128);
    make_map(enc, &p.m[2], d_in[3], 64, 512, 64, 1, 8192, 128, 8192 * 512, 64, 32, 2, 1, S128);
    make_map(enc, &p.m[3], d_in[1], 64, 8192, 8, 1, 1024, 128, 1024 * 8192, 64, 64, 1, 1, S128);
    make_map(enc, &p.m[4], d_in[4], 64, 64, 8, 64, 8192, 8192 * 64, 128, 64, 16, 2, 2, S128);
    make_map(enc, &p.m[5], d_in[5], 512, 4096, 1, 1, 1024, 1024 * 4096, 1024 * 4096, 16, 256, 1, 1, S32);
    make_map(enc, &p.m[6], d_in[7], 1376, 512, 1, 1, 2752, 2752 * 512, 2752 * 512, 16, 256, 1, 1, S32);
    make_map(enc, &p.m[7], d_in[9], 256, 2752, 1, 1, 512, 512 * 2752, 512 * 2752, 256, 16, 1, 1, S0);
    p.x = (const __nv_bfloat16*)d_in[0];
    p.c = (const __nv_bfloat16*)d_in[11];
    p.b1 = (const __nv_bfloat16*)d_in[8];
    p.b2 = (const __nv_bfloat16*)d_in[10];
    p.out = (__nv_bfloat16*)d_out;
    p.s = scratch;
    for (int i = 0; i < NTM; i++) p.tm[i] = g_tm[i];
    for (int i = 0; i < 32; i++) p.sched[i] = g_sched[i];
    fused_decode_kernel<<<NCTA, NTHR, SMEM_BYTES, cudaStreamPerThread>>>(p);
}
```

```cpp
#include <cuda_runtime.h>
#include <cuda_bf16.h>
#include <cuda.h>
#include <stdint.h>

namespace {

constexpr int NCTA   = 128;
constexpr int NFFN   = 86;
constexpr int NCHUNK = 32;
constexpr int NTHR   = 384;

#define MOD2_EARLY 1
constexpr int C_MOD1 = 0, C_WQ = 1, C_WUK = 5, C_CKV = 9, C_X = 17, C_WUV = 18, C_W1 = 28, C_W2 = 30;
constexpr int C_WO = MOD2_EARLY ? 24 : 22, C_MOD2 = MOD2_EARLY ? 22 : 26;

constexpr int S_WQ   = 0;
constexpr int S_WUK  = 32768;
constexpr int S_CKV  = 65536;
constexpr int S_WUV  = 131072;
constexpr int S_WO   = 163840;
constexpr int S_MOD2 = 196608;
constexpr int S_MOD1 = 212992;
constexpr int S_SC   = 221184;
constexpr int S_RED  = 223232;
constexpr int S_VEC  = 227328;
constexpr int S_R16  = 227840;
constexpr int S_MAX  = 228352;
constexpr int S_ONES = 229376;
constexpr int S_ML   = 230400;
constexpr int S_STAT = 230912;
constexpr int S_BAR  = 230976;
constexpr int S_EP   = 231312;
constexpr int S_B4   = 230912;
constexpr int S_TS   = 231328;
constexpr int S_END  = 231712;
constexpr int S_QABS = S_WQ, S_XBUF1 = S_WQ + 20480, S_XBUF0 = S_MOD1, S_XCH = S_WUK, S_GVEC = S_WQ, S_FVEC = S_WQ + 8192;
constexpr int S_W1 = S_WUK, S_W2 = S_WUK + 16384, S_P = S_MOD1, S_ALPHA = S_R16;
constexpr int B_UK = 32, B_QK = 33, B_X = 34, B_F = 36, B_BETA = 37, B_BETA4 = 38, B_W = 39, NBAR = 40;
constexpr int SMEM_BYTES = S_END;

#define POLMASK 0
#define KEEP_NS 200
#define KEEP_TAIL 2
#define WIN 5
enum { T_H1 = 0, T_H3, T_H4, D_H5, D_H6, D_H7, D_H4, D_ML, NTM = 8 };

constexpr uint32_t G_H1 = 0;
constexpr uint32_t G_H6 = 192 << 10;
constexpr uint32_t G_MOD2 = 16 << 10;
constexpr uint32_t G_ML = 48 << 10;
constexpr uint32_t G_PROBE = 88 << 10;
constexpr uint32_t G_H3 = 128 << 10;
constexpr uint32_t G_H2 = 256 << 10;
constexpr uint32_t G_H5 = 384 << 10;
constexpr uint32_t G_H7 = 512 << 10;
constexpr uint32_t G_EPOCH = 1 << 20;
constexpr uint32_t G_TS = (1 << 20) + 4096;
constexpr uint32_t G_H4 = 2 << 20;
constexpr uint32_t G_BYTES = 10 << 20;
__device__ __align__(256) unsigned char g_scratch[G_BYTES + (2 << 20)];
__device__ __forceinline__ uint32_t spread(uint32_t o) { return o + (o & ~4095u); }
__device__ __forceinline__ uint32_t pick(uint32_t po, uint32_t beta) {
    return po + (((beta ^ __popc(po & 0xB2000u)) & 1u) << 12);
}
#define TS(i) do {} while (0)
#define TS0(i) do {} while (0)
#define TS4(i) do {} while (0)

struct Params {
    const __nv_bfloat16* x;
    const __nv_bfloat16* c;
    const __nv_bfloat16* b1;
    const __nv_bfloat16* b2;
    __nv_bfloat16* out;
    unsigned char* s;
    uint16_t tm[NTM];
    uint16_t sched[32];
    CUtensorMap m[9];
};

constexpr int SPIN_MAX = 1 << 21;

__device__ __forceinline__ void mbar_init(uint32_t bar, uint32_t cnt) {
    asm volatile("mbarrier.init.shared::cta.b64 [%0], %1;" ::"r"(bar), "r"(cnt) : "memory");
}
__device__ __forceinline__ void mbar_expect_tx(uint32_t bar, uint32_t bytes) {
    asm volatile("mbarrier.arrive.expect_tx.shared::cta.b64 _, [%0], %1;" ::"r"(bar), "r"(bytes) : "memory");
}
__device__ __forceinline__ void mbar_arrive(uint32_t bar) {
    asm volatile("mbarrier.arrive.shared::cta.b64 _, [%0];" ::"r"(bar) : "memory");
}
__device__ __forceinline__ void mbar_wait(uint32_t bar) {
    asm volatile("{\n.reg .pred p;\nW:\nmbarrier.try_wait.parity.shared::cta.b64 p, [%0], 0;\n@!p bra W;\n}" ::"r"(bar) : "memory");
}
__device__ __forceinline__ void mbar_wait4(uint32_t bar) {
    asm volatile("{\n.reg .pred p, q, r, s;\nW:\n"
                 "mbarrier.try_wait.parity.shared::cta.b64 p, [%0], 0;\n"
                 "mbarrier.try_wait.parity.shared::cta.b64 q, [%0+8], 0;\n"
                 "mbarrier.try_wait.parity.shared::cta.b64 r, [%0+16], 0;\n"
                 "mbarrier.try_wait.parity.shared::cta.b64 s, [%0+24], 0;\n"
                 "and.pred p, p, q;\nand.pred r, r, s;\nand.pred p, p, r;\n@!p bra W;\n}" ::"r"(bar) : "memory");
}
__device__ __forceinline__ void mbar_wait_cluster(uint32_t bar) {
    asm volatile("{\n.reg .pred p;\nW:\nmbarrier.try_wait.parity.acquire.cluster.shared::cta.b64 p, [%0], 0;\n@!p bra W;\n}" ::"r"(bar) : "memory");
}
__device__ __forceinline__ void tma4(uint32_t dst, const CUtensorMap* m, int c0, int c1, int c2, int c3, uint32_t bar, uint64_t pol) {
    asm volatile("cp.async.bulk.tensor.4d.shared::cluster.global.mbarrier::complete_tx::bytes.L2::cache_hint [%0], [%1, {%3,%4,%5,%6}], [%2], %7;"
                 ::"r"(dst), "l"(m), "r"(bar), "r"(c0), "r"(c1), "r"(c2), "r"(c3), "l"(pol) : "memory");
}
__device__ __forceinline__ void bar_sync(int id, int n) { asm volatile("bar.sync %0, %1;" ::"r"(id), "r"(n) : "memory"); }
__device__ __forceinline__ void bar_arrive(int id, int n) { asm volatile("bar.arrive %0, %1;" ::"r"(id), "r"(n) : "memory"); }
__device__ __forceinline__ void fence_async() { asm volatile("fence.proxy.async.shared::cta;" ::: "memory"); }

__device__ __forceinline__ uint32_t ldr1(const void* p) {
    uint32_t v; asm volatile("ld.relaxed.gpu.global.u32 %0, [%1];" : "=r"(v) : "l"(p) : "memory"); return v;
}
__device__ __forceinline__ uint2 ldr2(const void* p) {
    uint2 v; asm volatile("ld.relaxed.gpu.global.v2.u32 {%0,%1}, [%2];" : "=r"(v.x), "=r"(v.y) : "l"(p) : "memory"); return v;
}
__device__ __forceinline__ uint4 ldr4(const void* p) {
    uint4 v; asm volatile("ld.relaxed.gpu.global.v4.u32 {%0,%1,%2,%3}, [%4];"
                          : "=r"(v.x), "=r"(v.y), "=r"(v.z), "=r"(v.w) : "l"(p) : "memory"); return v;
}
__device__ __forceinline__ void str1(void* p, uint32_t v) { asm volatile("st.relaxed.gpu.global.u32 [%0], %1;" ::"l"(p), "r"(v) : "memory"); }
__device__ __forceinline__ void str2(void* p, uint32_t a, uint32_t b) {
    asm volatile("st.relaxed.gpu.global.v2.u32 [%0], {%1,%2};" ::"l"(p), "r"(a), "r"(b) : "memory");
}
__device__ __forceinline__ void str4(void* p, uint32_t a, uint32_t b, uint32_t c, uint32_t d) {
    asm volatile("st.relaxed.gpu.global.v4.u32 [%0], {%1,%2,%3,%4};" ::"l"(p), "r"(a), "r"(b), "r"(c), "r"(d) : "memory");
}
__device__ __forceinline__ void str64(void* p, uint32_t a, uint32_t b) {
    asm volatile("{\n.reg .b64 t;\nmov.b64 t, {%1,%2};\nst.relaxed.gpu.global.b64 [%0], t;\n}" ::"l"(p), "r"(a), "r"(b) : "memory");
}
__device__ __forceinline__ void str64x2(void* p, uint32_t a, uint32_t b, uint32_t c, uint32_t d) {
    asm volatile("{\n.reg .b64 s, t;\nmov.b64 s, {%1,%2};\nmov.b64 t, {%3,%4};\nst.relaxed.gpu.global.v2.b64 [%0], {s,t};\n}" ::"l"(p), "r"(a), "r"(b), "r"(c), "r"(d) : "memory");
}
__device__ __forceinline__ uint4 ldr64x2(const void* p) {
    uint4 v; asm volatile("{\n.reg .b64 s, t;\nld.relaxed.gpu.global.v2.b64 {s,t}, [%4];\nmov.b64 {%0,%1}, s;\nmov.b64 {%2,%3}, t;\n}"
                          : "=r"(v.x), "=r"(v.y), "=r"(v.z), "=r"(v.w) : "l"(p) : "memory"); return v;
}
__device__ __forceinline__ uint32_t tagf(float v, uint32_t tg) { return (__float_as_uint(v) & ~1u) | tg; }
__device__ __forceinline__ float u2f(uint32_t v) { return __uint_as_float(v); }

__device__ __forceinline__ void sts1(uint32_t a, uint32_t v) { asm volatile("st.shared.u32 [%0], %1;" ::"r"(a), "r"(v) : "memory"); }
__device__ __forceinline__ void sts1f(uint32_t a, float v) { asm volatile("st.shared.f32 [%0], %1;" ::"r"(a), "f"(v) : "memory"); }
__device__ __forceinline__ void stsh(uint32_t a, uint32_t v) { asm volatile("st.shared.u16 [%0], %1;" ::"r"(a), "h"((unsigned short)v) : "memory"); }
__device__ __forceinline__ void sts2(uint32_t a, uint32_t x, uint32_t y) { asm volatile("st.shared.v2.u32 [%0], {%1,%2};" ::"r"(a), "r"(x), "r"(y) : "memory"); }
__device__ __forceinline__ void sts4(uint32_t a, uint32_t x, uint32_t y, uint32_t z, uint32_t w) {
    asm volatile("st.shared.v4.u32 [%0], {%1,%2,%3,%4};" ::"r"(a), "r"(x), "r"(y), "r"(z), "r"(w) : "memory");
}
__device__ __forceinline__ uint32_t lds1(uint32_t a) { uint32_t v; asm volatile("ld.shared.u32 %0, [%1];" : "=r"(v) : "r"(a) : "memory"); return v; }
__device__ __forceinline__ float lds1f(uint32_t a) { float v; asm volatile("ld.shared.f32 %0, [%1];" : "=f"(v) : "r"(a) : "memory"); return v; }
__device__ __forceinline__ float2 lds2f(uint32_t a) { float2 v; asm volatile("ld.shared.v2.f32 {%0,%1}, [%2];" : "=f"(v.x), "=f"(v.y) : "r"(a) : "memory"); return v; }
__device__ __forceinline__ uint4 lds4(uint32_t a) {
    uint4 v; asm volatile("ld.shared.v4.u32 {%0,%1,%2,%3}, [%4];" : "=r"(v.x), "=r"(v.y), "=r"(v.z), "=r"(v.w) : "r"(a) : "memory"); return v;
}
__device__ __forceinline__ float4 lds4f(uint32_t a) {
    float4 v; asm volatile("ld.shared.v4.f32 {%0,%1,%2,%3}, [%4];" : "=f"(v.x), "=f"(v.y), "=f"(v.z), "=f"(v.w) : "r"(a) : "memory"); return v;
}
__device__ __forceinline__ void ldsm4(uint32_t a, uint32_t (&r)[4]) {
    asm volatile("ldmatrix.sync.aligned.m8n8.x4.shared.b16 {%0,%1,%2,%3}, [%4];"
                 : "=r"(r[0]), "=r"(r[1]), "=r"(r[2]), "=r"(r[3]) : "r"(a) : "memory");
}
__device__ __forceinline__ void ldsm4t(uint32_t a, uint32_t (&r)[4]) {
    asm volatile("ldmatrix.sync.aligned.m8n8.x4.trans.shared.b16 {%0,%1,%2,%3}, [%4];"
                 : "=r"(r[0]), "=r"(r[1]), "=r"(r[2]), "=r"(r[3]) : "r"(a) : "memory");
}
__device__ __forceinline__ void stsm4t(uint32_t a, uint32_t r0, uint32_t r1, uint32_t r2, uint32_t r3) {
    asm volatile("stmatrix.sync.aligned.m8n8.x4.trans.shared.b16 [%0], {%1,%2,%3,%4};"
                 ::"r"(a), "r"(r0), "r"(r1), "r"(r2), "r"(r3) : "memory");
}
__device__ __forceinline__ void mma16816(float (&d)[4], const uint32_t (&a)[4], uint32_t b0, uint32_t b1) {
    asm volatile("mma.sync.aligned.m16n8k16.row.col.f32.bf16.bf16.f32 {%0,%1,%2,%3}, {%4,%5,%6,%7}, {%8,%9}, {%0,%1,%2,%3};"
                 : "+f"(d[0]), "+f"(d[1]), "+f"(d[2]), "+f"(d[3])
                 : "r"(a[0]), "r"(a[1]), "r"(a[2]), "r"(a[3]), "r"(b0), "r"(b1));
}
__device__ __forceinline__ uint32_t packbf(float lo, float hi) {
    uint32_t r; asm("cvt.rn.bf16x2.f32 %0, %1, %2;" : "=r"(r) : "f"(hi), "f"(lo)); return r;
}
__device__ __forceinline__ float bflo(uint32_t w) { return __uint_as_float(w << 16); }
__device__ __forceinline__ float bfhi(uint32_t w) { return __uint_as_float(w & 0xffff0000u); }
__device__ __forceinline__ void split2(float a, float b, uint32_t& hi, uint32_t& lo) {
    hi = packbf(a, b);
    lo = packbf(a - bflo(hi), b - bfhi(hi));
}
__device__ __forceinline__ uint32_t ordf(uint32_t u) { return u ^ ((uint32_t)((int)u >> 31) & 0x7FFFFFFFu); }
__device__ __forceinline__ void red_max(uint32_t a, uint32_t v) { asm volatile("red.shared.max.s32 [%0], %1;" ::"r"(a), "r"(v) : "memory"); }
__device__ __forceinline__ float fsel(bool c, float a, float b) {
    float r; asm("{\n.reg .pred p;\nsetp.ne.b32 p, %3, 0;\nselp.f32 %0, %1, %2, p;\n}" : "=f"(r) : "f"(a), "f"(b), "r"((int)c)); return r;
}
__device__ __forceinline__ float ex2(float x) { float y; asm("ex2.approx.ftz.f32 %0, %1;" : "=f"(y) : "f"(x)); return y; }

__device__ __forceinline__ int vpos(int k32) {
    return (((k32 & 7) >> 1) * 8 + (k32 >> 4) * 4 + ((k32 >> 3) & 1) * 2 + (k32 & 1)) * 2;
}

__device__ __forceinline__ void wg_fence()  { asm volatile("wgmma.fence.sync.aligned;" ::: "memory"); }
__device__ __forceinline__ void wg_commit() { asm volatile("wgmma.commit_group.sync.aligned;" ::: "memory"); }
template <int N> __device__ __forceinline__ void wg_wait() { asm volatile("wgmma.wait_group.sync.aligned %0;" ::"n"(N) : "memory"); }
__device__ __forceinline__ uint64_t mkdesc(uint32_t addr) {
    return (uint64_t)((addr & 0x3FFFF) >> 4) | ((uint64_t)64 << 16) | ((uint64_t)64 << 32) | ((uint64_t)1 << 62);
}
template <int TA>
__device__ __forceinline__ void wgmma_n32(float (&d)[16], uint64_t da, uint64_t db, int acc) {
    asm volatile("{\n.reg .pred p;\nsetp.ne.b32 p, %18, 0;\n"
                 "wgmma.mma_async.sync.aligned.m64n32k16.f32.bf16.bf16 "
                 "{%0,%1,%2,%3,%4,%5,%6,%7,%8,%9,%10,%11,%12,%13,%14,%15}, %16, %17, p, 1, 1, %19, 0;\n}"
                 : "+f"(d[0]), "+f"(d[1]), "+f"(d[2]), "+f"(d[3]), "+f"(d[4]), "+f"(d[5]), "+f"(d[6]), "+f"(d[7]),
                   "+f"(d[8]), "+f"(d[9]), "+f"(d[10]), "+f"(d[11]), "+f"(d[12]), "+f"(d[13]), "+f"(d[14]), "+f"(d[15])
                 : "l"(da), "l"(db), "r"(acc), "n"(TA));
}
__device__ __forceinline__ void reg_fence16(float (&d)[16]) {
#pragma unroll
    for (int i = 0; i < 16; i++) asm volatile("" : "+f"(d[i])::"memory");
}

template <bool TRANS>
__device__ __forceinline__ void gemv128(uint32_t tile, uint32_t vec, uint32_t bars, int warp, int lane, float& r0, float& r1) {
    const int m = lane >> 3, r8 = lane & 7;
    uint32_t bq[4][4];
#pragma unroll
    for (int i = 0; i < 4; i++) {
        uint4 t = lds4(vec + i * 128 + ((lane >> 2) & 1) * 64 + (lane & 3) * 16);
        bq[i][0] = t.x; bq[i][1] = t.y; bq[i][2] = t.z; bq[i][3] = t.w;
    }
    float d0[4] = {0.f, 0.f, 0.f, 0.f}, d1[4] = {0.f, 0.f, 0.f, 0.f};
    if (TRANS) {
        const uint32_t a0 = tile + (warp >> 2) * 4096 + ((m >> 1) * 8 + r8) * 128 + ((((warp & 3) * 2 + (m & 1)) ^ r8) << 4);
#pragma unroll
        for (int i = 0; i < 4; i++) {
            mbar_wait(bars + i * 8);
            uint32_t a[4], c[4];
            ldsm4t(a0 + i * 8192, a);
            ldsm4t(a0 + i * 8192 + 2048, c);
            mma16816(d0, a, bq[i][0], bq[i][1]);
            mma16816(d1, c, bq[i][2], bq[i][3]);
        }
    } else {
        mbar_wait(bars + (warp >> 1) * 8);
        const uint32_t a0 = tile + (warp >> 1) * 8192 + ((warp & 1) * 16 + (m & 1) * 8 + r8) * 128;
#pragma unroll
        for (int i = 0; i < 4; i++) {
            uint32_t a[4], c[4];
            ldsm4(a0 + (i >> 1) * 4096 + ((((i & 1) * 4 + (m >> 1)) ^ r8) << 4), a);
            ldsm4(a0 + (i >> 1) * 4096 + ((((i & 1) * 4 + 2 + (m >> 1)) ^ r8) << 4), c);
            mma16816(d0, a, bq[i][0], bq[i][1]);
            mma16816(d1, c, bq[i][2], bq[i][3]);
        }
    }
    r0 = (d0[0] + d0[1]) + (d1[0] + d1[1]);
    r1 = (d0[2] + d0[3]) + (d1[2] + d1[3]);
}

__device__ __forceinline__ void step32(uint32_t rows, uint32_t vecaddr, int lane, float (&d0)[4], float (&d1)[4]) {
    const int m = lane >> 3, r8 = lane & 7;
    const uint32_t a0 = rows + ((m >> 1) * 8 + r8) * 32 + (((m & 1) ^ (r8 >> 2)) << 4);
    uint4 t = lds4(vecaddr);
    uint32_t a[4], c[4];
    ldsm4t(a0, a);
    ldsm4t(a0 + 512, c);
    mma16816(d0, a, t.x, t.y);
    mma16816(d1, c, t.z, t.w);
}

__device__ __forceinline__ void reduce16_publish(uint32_t sb, float (&d0)[4], float (&d1)[4], int tid, int warp, int lane, unsigned char* dst, uint32_t tg) {
    if ((lane & 3) == 0) {
        sts1f(sb + S_R16 + (lane >> 2) * 32 + warp * 4, (d0[0] + d0[1]) + (d1[0] + d1[1]));
        sts1f(sb + S_R16 + ((lane >> 2) + 8) * 32 + warp * 4, (d0[2] + d0[3]) + (d1[2] + d1[3]));
    }
    bar_sync(2, 256);
    if (tid < 32) {
        float4 u = lds4f(sb + S_R16 + (tid & 15) * 32), v = lds4f(sb + S_R16 + (tid & 15) * 32 + 16);
        str1(dst + (tid & 15) * 4 + (tid >> 4) * 4096, tagf(((u.x + u.y) + (u.z + u.w)) + ((v.x + v.y) + (v.z + v.w)), tg));
    }
}

__device__ __forceinline__ uint32_t xo2(uint32_t a, uint32_t b, uint32_t t) {
    uint32_t r; asm("lop3.b32 %0, %1, %2, %3, 0x7E;" : "=r"(r) : "r"(a), "r"(b), "r"(t)); return r;
}
__device__ __forceinline__ uint32_t or3(uint32_t a, uint32_t b, uint32_t c) {
    uint32_t r; asm("lop3.b32 %0, %1, %2, %3, 0xFE;" : "=r"(r) : "r"(a), "r"(b), "r"(c)); return r;
}
__device__ __forceinline__ uint32_t bad2(const uint2& v, uint32_t tg) { return xo2(v.x, v.y, tg); }
__device__ __forceinline__ uint32_t bad4(const uint4& v, uint32_t tg) { return or3(xo2(v.x, v.y, tg), xo2(v.z, v.w, tg), 0); }
__device__ __forceinline__ bool nz4(const uint4& v) { return v.x != 0 && v.y != 0 && v.z != 0 && v.w != 0; }
__device__ __forceinline__ uint32_t clk32() { uint32_t c; asm volatile("mov.u32 %0, %%clock;" : "=r"(c)); return c; }
__device__ __forceinline__ void wait_until(uint32_t t0, uint32_t dt) {
#pragma unroll 1
    while (clk32() - t0 < dt) {}
}
__device__ __forceinline__ uint32_t mbar_mask4(uint32_t bar) {
    uint32_t m;
    asm volatile("{\n.reg .pred p, q, r, s;\n.reg .b32 a, b;\n"
                 "mbarrier.test_wait.parity.shared::cta.b64 p, [%1], 0;\n"
                 "mbarrier.test_wait.parity.shared::cta.b64 q, [%1+8], 0;\n"
                 "mbarrier.test_wait.parity.shared::cta.b64 r, [%1+16], 0;\n"
                 "mbarrier.test_wait.parity.shared::cta.b64 s, [%1+24], 0;\n"
                 "selp.u32 a, 1, 0, p;\nselp.u32 b, 2, 0, q;\nor.b32 a, a, b;\nselp.u32 b, 4, 0, r;\nor.b32 a, a, b;\n"
                 "selp.u32 b, 8, 0, s;\nor.b32 a, a, b;\nredux.sync.and.b32 %0, a, 0xffffffff;\n}" : "=r"(m) : "r"(bar) : "memory");
    return m;
}
__device__ __forceinline__ uint32_t probe_near(unsigned char* sp, uint32_t po, uint32_t sink) {
    uint32_t best0 = ~0u, best1 = ~0u;
#pragma unroll 1
    for (int r = 0; r < 5; r++) {
        uint32_t v; const uint32_t t0 = clk32();
        asm volatile("atom.relaxed.gpu.global.exch.b32 %0, [%1], %2;" : "=r"(v) : "l"(sp + po + (r & 1) * 4096), "r"(r) : "memory");
        sts1(sink, v);
        const uint32_t dt = clk32() - t0;
        if (r & 1) best1 = min(best1, dt); else best0 = min(best0, dt);
    }
    return (uint32_t)(best1 < best0) ^ (__popc(po & 0xB2000u) & 1u);
}
#define mbar_wait_init(sb) bar_sync(8, 64)
#define PIN(x) asm volatile("" : "+l"(x))
#define SPIN_CHECK(it) if (++(it) > SPIN_MAX) __trap()

__device__ __forceinline__ void mod2_tile(uint32_t sb, unsigned char* sp, uint32_t bars, int b, int nt, int lane, uint32_t tg) {
    const int m = lane >> 3, r8 = lane & 7, q = lane & 3;
    const uint32_t a0 = sb + S_MOD2 + ((m >> 1) * 8 + r8) * 64 + (((nt * 2 + (m & 1)) ^ (r8 >> 1)) << 4);
    const uint32_t v0 = sb + S_SC + (b >> 6) * 1024 + ((lane >> 2) & 1) * 64 + q * 16;
    float d0[4] = {0.f, 0.f, 0.f, 0.f}, d1[4] = {0.f, 0.f, 0.f, 0.f};
#pragma unroll 1
    for (int c = 0; c < 2; c++) {
        mbar_wait(bars + (C_MOD2 + c) * 8);
#pragma unroll
        for (int i = 0; i < 4; i++) {
            const uint4 t = lds4(v0 + (c * 4 + i) * 128);
            uint32_t a[4], e[4];
            ldsm4t(a0 + c * 8192 + i * 2048, a); ldsm4t(a0 + c * 8192 + i * 2048 + 1024, e);
            mma16816(d0, a, t.x, t.y); mma16816(d1, e, t.z, t.w);
        }
    }
    const float r0 = (d0[0] + d0[1]) + (d1[0] + d1[1]), r1 = (d0[2] + d0[3]) + (d1[2] + d1[3]);
    const float t0 = __shfl_sync(~0u, r0, lane & 28), t1 = __shfl_sync(~0u, r1, lane & 28);
    str1(sp + G_MOD2 + spread(b * 128 + nt * 64 + (q & 1) * 32 + (lane >> 2) * 4) + (q >> 1) * 4096, tagf((q & 1) ? t1 : t0, tg));
}

__global__ void __cluster_dims__(2, 1, 1) __launch_bounds__(NTHR, 1) fused_decode_kernel(const __grid_constant__ Params p) {
    extern __shared__ __align__(1024) unsigned char smem_raw[];
    const uint32_t sb = (uint32_t)__cvta_generic_to_shared(smem_raw);
    const int tid = threadIdx.x, lane = tid & 31;
    const int warp = __shfl_sync(~0u, tid >> 5, 0);
    const int b = blockIdx.x, h = b >> 2, j = b & 3, rank = b & 1, pair = b >> 1;
    const uint32_t bars = sb + S_BAR;
    unsigned char* const sp = p.s;
    const uint32_t t_start = clk32();

    if (warp == 11) {
        float d[4] = {0.f, 0.f, 0.f, 0.f};
        const uint32_t zz = t_start & 0x00010001u, z[4] = {zz, zz, zz, zz};
        mma16816(d, z, zz, zz);
        bar_sync(1, NTHR - 32);
        uint32_t done = 0;
#pragma unroll 1
        for (int i = 0; i < 4096 && done < KEEP_TAIL; i++) {
            mma16816(d, z, zz, zz);
            __nanosleep(KEEP_NS);
            done += mbar_mask4(bars + B_F * 8) & 1;
        }
        if (d[0] == 1.f) sts1f(sb + S_EP + 12, d[1]);
        return;
    }
    if (warp == 8) {
        TS(30);
        uint64_t pol_first, pol_norm;
        asm("createpolicy.fractional.L2::evict_first.b64 %0, 1.0;" : "=l"(pol_first));
        asm("createpolicy.fractional.L2::evict_normal.b64 %0, 1.0;" : "=l"(pol_norm));
        if (lane == 0) {
            mbar_init(bars, 1);
            asm volatile("fence.mbarrier_init.release.cluster;" ::: "memory");
            mbar_expect_tx(bars, 8192);
            tma4(sb + S_MOD1, &p.m[0], (b >> 1) * 16, (b & 1) * 256, 0, 0, bars, (POLMASK & 1) ? pol_norm : pol_first);
            TS(28);
#pragma unroll
            for (int i = 1; i < NBAR; i++) mbar_init(bars + i * 8, i == B_UK ? 8 : 1);
            asm volatile("fence.mbarrier_init.release.cluster;" ::: "memory");
            mbar_expect_tx(bars + B_X * 8, 8192); mbar_expect_tx(bars + (B_X + 1) * 8, 8192);
        }
        __syncwarp();
        TS(27);
        bar_arrive(1, NTHR - 32);
        {
            const int c = lane;
            int mi = 1, k = c - C_WQ, c0 = 0, c1 = j * 128, d1 = 32, c2 = h * 2, c3 = 0, dst = S_WQ;
            if (c >= C_WUK)  { mi = 2; k = c - C_WUK; dst = S_WUK; }
            if (c >= C_CKV)  { mi = 3; k = c - C_CKV; dst = S_CKV; c1 = pair * 128 + (k >> 2) * 64; d1 = 0; c2 = rank * 4 + (k & 3); }
            if (c == C_X)    { dst = S_XCH - 8 * 8192; c1 = pair * 128 + 64; c2 = (rank ^ 1) * 4 + 3; }
            if (c >= C_WUV)  { mi = 4; k = c - C_WUV; dst = S_WUV; c1 = j * 16; c2 = k * 2; c3 = h * 2; }
            if (c >= C_WUV + 4) { mi = 5; k = c - C_WO; dst = S_WO; c0 = (b & 15) * 32; c1 = (b >> 4) * 512; d1 = 128; c2 = 0; c3 = 0; }
            if (c == C_MOD2 || c == C_MOD2 + 1) { mi = 8; k = c - C_MOD2; dst = S_MOD2; c0 = 1024 + (b & 63) * 32; c1 = (b >> 6) * 256; }
            if (c >= C_W1)   { mi = 6; k = c - C_W1; dst = S_W1; c0 = b * 16; c1 = 0; d1 = 256; }
            if (c >= C_W2)   { mi = 7; k = c - C_W2; dst = S_W2; c0 = 0; c1 = b * 32; d1 = 16; }
            const uint32_t wa = (uint32_t)c0 | (uint32_t)(c1 + k * d1) << 16;
            const bool keep = (POLMASK >> mi & 1) || c == C_X || c == C_X - 1;
            const uint32_t wb = (uint32_t)c2 | (uint32_t)c3 << 8 | (uint32_t)mi << 14 | (uint32_t)keep << 18 | (uint32_t)((dst >> 13) + k) << 24;
            const int nch = b < NFFN ? NCHUNK : C_W1;
#pragma unroll 1
            for (int i = 1; i < nch; i++) {
                const uint32_t ua = __shfl_sync(~0u, wa, i), ub = __shfl_sync(~0u, wb, i);
                if (i == C_X) mbar_wait(bars + B_UK * 8);
                if (i == C_W1) mbar_wait(bars + B_QK * 8);
                if (i >= WIN) mbar_wait(bars + (i - WIN) * 8);
                wait_until(t_start, p.sched[i]);
                if (lane == 0) {
                    mbar_expect_tx(bars + i * 8, 8192);
                    tma4(sb + (ub >> 24) * 8192, &p.m[(ub >> 14) & 15], ua & 0xffff, ua >> 16, ub & 0xff, (ub >> 8) & 0x3f, bars + i * 8,
                         (ub >> 18 & 1) ? pol_norm : pol_first);
                }
            }
        }
        TS(20);
        return;
    }
    if (warp == 9) {
        const int e = lane & 3;
        const float xe = __bfloat162float(p.x[b * 4 + e]), be = __bfloat162float(p.b2[b * 4 + e]);
        const uint32_t pr0 = G_PROBE + b * 32, pr4 = G_H4 + pair * 131072 + 65536 + rank * 256;
        if (lane < 4) str4(sp + pr0 + (lane & 2) * 2048 + (lane & 1) * 16, 0, 0, 0, 0);
        __syncwarp();
        uint32_t beta = 0;
                if (lane == 0) { beta = probe_near(sp, pr0, sb + S_EP + 12); sts1(sb + S_EP + 4, beta); }
        __syncwarp();
        mbar_wait_init(sb);
        if (lane == 0) mbar_arrive(bars + B_BETA * 8);
        TS(69);
        const uint32_t ep = lds1(sb + S_EP);
        const uint32_t tg = ~ep & 1u;
        beta = __shfl_sync(~0u, beta, 0);
        {
            const uint32_t prev = ldr1(sp + pr4 + 128);
            if (lane < 4) str4(sp + pr4 + (lane & 2) * 2048 + (lane & 1) * 16, 0, 0, 0, 0);
            __syncwarp();
            uint32_t w = 0;
            if (lane == 0) {
                                const uint32_t beta4 = probe_near(sp, pr4, sb + S_EP + 12);
                const uint32_t held = (prev & 24) ^ (8u << beta4);
                w = tg | beta4 << 1 | (held >> (3 + beta4) & 1) << 2 | held;
                sts1(sb + S_EP + 8, w);
                mbar_arrive(bars + B_BETA4 * 8);
            }
            w = __shfl_sync(~0u, w, 0);
            if (lane < 2) str4(sp + pr4 + 128 + lane * 16, w, w, w, w);
        }
        TS(70);
        const unsigned char* s6 = sp + pick(G_H6 + spread((lane >> 2) * 2048 + b * 16 + e * 4), beta);
        const unsigned char* sg = sp + pick(G_MOD2 + spread((lane & 4) * 2048 + ((lane & 8) ? 6144 : 0) + b * 16 + e * 4), beta);
        const unsigned char* s7 = sp + pick(G_H7 + spread(lane * 2048 + b * 16), beta);
        const unsigned char* s7b = sp + pick(G_H7 + spread((lane + 32) * 2048 + b * 16), beta);
        const unsigned char* s7c = sp + pick(G_H7 + spread((lane < NFFN - 64 ? lane + 64 : lane) * 2048 + b * 16), beta);
        mod2_tile(sb, sp, bars, b, 0, lane, tg);
        TS(29);
        mbar_wait(bars + B_F * 8);
        wait_until(clk32(), p.tm[D_H6]);
        uint32_t v, w; int it = 0;
#pragma unroll 1
        do { v = ldr1(s6); w = ldr1(sg); SPIN_CHECK(it); } while (__any_sync(~0u, xo2(v, w, tg) & 1));
        const uint32_t t_6 = clk32();
        float o = u2f(v), gg = u2f(w);
        o += __shfl_xor_sync(~0u, o, 4); gg += __shfl_xor_sync(~0u, gg, 4);
        o += __shfl_xor_sync(~0u, o, 8); o += __shfl_xor_sync(~0u, o, 16);
        const float gb = __shfl_sync(~0u, gg, 8 + e);
        const float x2 = fmaf(gb, be, fmaf(gg, o, xe));
        TS(21);
        wait_until(t_6, p.tm[D_H7]);
        uint4 y0, y1, y2;
#pragma unroll 1
        do {
            y0 = ldr4(s7); y1 = ldr4(s7b); y2 = ldr4(s7c);
            SPIN_CHECK(it);
        } while (__any_sync(~0u, or3(bad4(y0, tg), bad4(y1, tg), bad4(y2, tg)) & 1));
        if (lane >= NFFN - 64) y2 = make_uint4(0, 0, 0, 0);
        const float s0 = (u2f(y0.x) + u2f(y1.x)) + u2f(y2.x), s1 = (u2f(y0.y) + u2f(y1.y)) + u2f(y2.y);
        const float s2 = (u2f(y0.z) + u2f(y1.z)) + u2f(y2.z), s3 = (u2f(y0.w) + u2f(y1.w)) + u2f(y2.w);
        {
            const bool b1 = lane & 2, b0 = lane & 1;
            const float k0 = (b1 ? s2 : s0) + __shfl_xor_sync(~0u, b1 ? s0 : s2, 2), k1 = (b1 ? s3 : s1) + __shfl_xor_sync(~0u, b1 ? s1 : s3, 2);
            float k = (b0 ? k1 : k0) + __shfl_xor_sync(~0u, b0 ? k0 : k1, 1);
            k += __shfl_xor_sync(~0u, k, 4); k += __shfl_xor_sync(~0u, k, 8); k += __shfl_xor_sync(~0u, k, 16);
            if (lane < 4) p.out[b * 4 + lane] = __float2bfloat16(fmaf(gb, k, x2));
            if (b == 0 && lane == 4) str1(sp + G_EPOCH, ep + 1);
        }
        TS(22);
        return;
    }

    if (warp == 10) {
        const float b1v = __bfloat162float(p.b1[(b < NFFN ? b * 16 : 0) + (lane & 15)]);
        bar_sync(1, NTHR - 32);
        const uint32_t tg = ~lds1(sb + S_EP) & 1u;
        mbar_wait(bars + B_BETA * 8);
        const uint32_t beta = lds1(sb + S_EP + 4);
        const unsigned char* sm_a = sp + pick(G_ML + spread(lane * 256 + h * 4), beta);
        const unsigned char* sm_b = sp + pick(G_ML + spread((lane + 32) * 256 + h * 4), beta);
        mbar_wait(bars + B_QK * 8);
        wait_until(clk32(), p.tm[D_ML]);
        wait_until(t_start, p.tm[T_H4] - 80);
        uint32_t ma, mb, la, lb; int it = 0;
        TS(76);
#pragma unroll 1
        do {
            ma = ldr1(sm_a); mb = ldr1(sm_b); la = ldr1(sm_a + 128); lb = ldr1(sm_b + 128);
            SPIN_CHECK(it);
        } while (__any_sync(~0u, (xo2(ma, mb, tg) | xo2(la, lb, tg)) & 1));
        TS(77);
        float M = fmaxf(u2f(ma), u2f(mb));
#pragma unroll
        for (int o = 16; o; o >>= 1) M = fmaxf(M, __shfl_xor_sync(~0u, M, o));
        const float wa = ex2(u2f(ma) - M), wb = ex2(u2f(mb) - M);
        float L = wa * u2f(la) + wb * u2f(lb);
#pragma unroll
        for (int o = 16; o; o >>= 1) L += __shfl_xor_sync(~0u, L, o);
        L = __fdividef(1.f, L);
        sts1f(sb + S_ML + lane * 4, wa * L); sts1f(sb + S_ML + 128 + lane * 4, wb * L);
        __syncwarp();
        if (lane == 0) mbar_arrive(bars + B_W * 8);
        TS(78);
        mod2_tile(sb, sp, bars, b, 1, lane, tg);
        if (b < NFFN) {
            const uint32_t a = sb + S_RED + (lane & 15) * 32 + (lane >> 4) * 16;
            const uint32_t as = sb + S_RED + 1536 + (lane >> 4) * 16;
            bar_sync(9, 288);
            const float4 sa = lds4f(as + 8 * 32), ta = lds4f(as + 6 * 32), tc = lds4f(as + 7 * 32);
            const float4 U = lds4f(a), G = lds4f(a + 512), S = lds4f(a + 1024);
            float mu = (sa.x + sa.y) + (sa.z + sa.w), ex = ((ta.x + ta.y) + (ta.z + ta.w)) + ((tc.x + tc.y) + (tc.z + tc.w));
            float us = (U.x + U.y) + (U.z + U.w), gs = (G.x + G.y) + (G.z + G.w), ss = (S.x + S.y) + (S.z + S.w);
            mu += __shfl_xor_sync(~0u, mu, 16); ex += __shfl_xor_sync(~0u, ex, 16);
            us += __shfl_xor_sync(~0u, us, 16); gs += __shfl_xor_sync(~0u, gs, 16); ss += __shfl_xor_sync(~0u, ss, 16);
            mu *= 1.f / 512.f;
            float rstd;
            asm("rsqrt.approx.ftz.f32 %0, %1;" : "=f"(rstd) : "f"(fmaxf(fmaf(ex, 1.f / 512.f, -mu * mu), 0.f) + 1e-5f));
            const float pre = (us - mu * gs) * rstd + (ss + b1v);
            const float z = pre * fmaf(pre * pre, 0.044715f * 2.302208198f, 2.302208198f);
            sts1f(sb + S_STAT + (lane & 15) * 4, __fdividef(pre, 1.f + ex2(fminf(-z, 126.f))));
            bar_arrive(10, 288);
        }
        return;
    }

    const int g = lane >> 2, q = lane & 3;
    const int wg = warp >> 2, wq = warp & 3;
    const uint32_t ep0 = ldr1(sp + G_EPOCH);
    const uint32_t tg = ~ep0 & 1u;
    const uint32_t cw = *reinterpret_cast<const uint32_t*>(p.c + tid * 2);
    const uint4 xa = *reinterpret_cast<const uint4*>(p.x + lane * 16), xb = *reinterpret_cast<const uint4*>(p.x + lane * 16 + 8);
    const uint32_t xw2 = *reinterpret_cast<const uint32_t*>(p.x + tid * 2);
    const float xm = __bfloat162float(p.x[j * 128 + (tid & 127)]);
    {
        uint32_t z = ~0u, zv = tg ^ 1u;
        if (tid < 4) z = G_H1 + spread((b & 1) * 4096 + (b >> 1) * 64 + tid * 16);
        else if (tid >= 8 && tid < 16) z = G_MOD2 + spread(b * 128 + (tid & 7) * 16);
        else if (tid >= 112 && tid < 120) z = G_H6 + spread(b * 128 + (tid & 7) * 16);
        else if (tid >= 16 && tid < 32) { const uint32_t o = G_ML + spread(pair * 256 + (tid & 15) * 16) + rank * 4096; str4(sp + o, zv, zv, zv, zv); }
        else if (tid >= 32 && tid < 64) z = G_H2 + spread(b * 512 + lane * 16);
        else if (tid >= 64 && tid < 96) z = G_H5 + spread(b * 512 + lane * 16);
        else if (tid >= 96 && tid < 112) { z = G_H3 + spread((j * 2 + ((tid >> 3) & 1)) * 4096 + h * 128 + (tid & 7) * 16); zv = 0; }
        else if (tid >= 128 && b < NFFN) z = G_H7 + spread(b * 2048 + (tid - 128) * 16);
        if (z != ~0u) { str4(sp + z, zv, zv, zv, zv); str4(sp + z + 4096, zv, zv, zv, zv); }
    }
    if (tid == 0) sts1(sb + S_EP, ep0);
    if (tid < 64) sts1(sb + S_MAX + tid * 4, 0x80000000u);
    sts1(sb + S_ONES + tid * 4, 0x3F803F80u);
    {
        const float c0 = bflo(cw), c1 = bfhi(cw);
        const float s0 = __fdividef(c0, 1.f + __expf(fminf(-c0, 80.f))), s1 = __fdividef(c1, 1.f + __expf(fminf(-c1, 80.f)));
        uint32_t hi, lo; split2(s0, s1, hi, lo);
        const uint32_t a = sb + S_SC + (tid >> 4) * 128 + vpos((tid & 15) * 2);
        sts1(a, hi); sts1(a + 64, lo);
    }
    TS0(0);
    bar_sync(1, NTHR - 32);
    if (warp == 7) bar_arrive(8, 64);

    const uint32_t vlane = (g & 1) * 64 + q * 16;

    {
        float d0[4] = {0.f, 0.f, 0.f, 0.f}, d1[4] = {0.f, 0.f, 0.f, 0.f};
        mbar_wait(bars + C_MOD1 * 8);
        step32(sb + S_MOD1 + warp * 1024, sb + S_SC + ((b & 1) * 8 + warp) * 128 + vlane, lane, d0, d1);
        reduce16_publish(sb, d0, d1, tid, warp, lane, sp + G_H1 + spread((b & 1) * 4096 + (b >> 1) * 64), tg);
    }
    TS0(1);
    float mean1, rstd1;
    {
        const uint32_t w[8] = {xa.x, xa.y, xa.z, xa.w, xb.x, xb.y, xb.z, xb.w};
        float s = 0.f;
#pragma unroll
        for (int i = 0; i < 8; i++) s += bflo(w[i]) + bfhi(w[i]);
#pragma unroll
        for (int o = 16; o; o >>= 1) s += __shfl_xor_sync(~0u, s, o);
        mean1 = s * (1.f / 512.f);
        float v = 0.f;
#pragma unroll
        for (int i = 0; i < 8; i++) { float a = bflo(w[i]) - mean1, c = bfhi(w[i]) - mean1; v += a * a + c * c; }
#pragma unroll
        for (int o = 16; o; o >>= 1) v += __shfl_xor_sync(~0u, v, o);
        rstd1 = rsqrtf(v * (1.f / 512.f) + 1e-5f);
    }
    if (tid < 128) {
        const unsigned char* s0 = sp + G_H1 + j * 512 + tid * 4;
        const unsigned char* s1 = s0 + 8192;
        uint4 a; int it = 0;
        wait_until(t_start, p.tm[T_H1]);
#pragma unroll 1
        do {
            a.x = ldr1(s0); a.y = ldr1(s1); a.z = ldr1(s0 + 2048); a.w = ldr1(s1 + 2048);
            SPIN_CHECK(it);
        } while (bad4(a, tg) & 1);
        const float hv = (xm - mean1) * rstd1 * (1.f + (u2f(a.z) + u2f(a.w))) + (u2f(a.x) + u2f(a.y));
        uint32_t hi, lo; split2(hv, 0.f, hi, lo);
        const uint32_t ad = sb + S_VEC + (tid >> 5) * 128 + vpos(tid & 31);
        stsh(ad, hi); stsh(ad + 64, lo);
    }
    TS0(2);
    bar_sync(2, 256);
    {
        float r0, r1;
        gemv128<true>(sb + S_WQ, sb + S_VEC, bars + C_WQ * 8, warp, lane, r0, r1);
        const float t0 = __shfl_sync(~0u, r0, lane & 28), t1 = __shfl_sync(~0u, r1, lane & 28);
        str1(sp + G_H2 + spread(b * 512 + warp * 64 + (q & 1) * 32 + g * 4) + (q >> 1) * 4096, tagf((q & 1) ? t1 : t0, tg));
    }
    TS0(3);
    mbar_wait(bars + B_BETA * 8);
    const uint32_t beta = lds1(sb + S_EP + 4);
    bar_sync(2, 256);
    if (tid < 128) {
        const unsigned char* src = sp + pick(G_H2 + spread(h * 2048 + tid * 4), beta);
        uint4 a; int it = 0;
#pragma unroll 1
        do {
            a.x = ldr1(src); a.y = ldr1(src + 512); a.z = ldr1(src + 1024); a.w = ldr1(src + 1536);
            SPIN_CHECK(it);
        } while (bad4(a, tg) & 1);
        const float qv = ((u2f(a.x) + u2f(a.y)) + (u2f(a.z) + u2f(a.w))) * (0.08838834764831845f * 1.4426950408889634f);
        uint32_t hi, lo; split2(qv, 0.f, hi, lo);
        const uint32_t ad = sb + S_VEC + (tid >> 5) * 128 + vpos(tid & 31);
        stsh(ad, hi); stsh(ad + 64, lo);
    }
    TS0(4);
    bar_sync(2, 256);
    {
        float r0, r1;
        gemv128<false>(sb + S_WUK, sb + S_VEC, bars + C_WUK * 8, warp, lane, r0, r1);
        const float n0 = __shfl_down_sync(~0u, r0, 4), m0 = __shfl_up_sync(~0u, r1, 4);
        const uint32_t w = (g & 1) ? packbf(m0, r1) : packbf(r0, n0);
        const uint32_t w2 = __shfl_sync(~0u, w, lane & 28);
        if (q < 2) {
            const int chunk = ((warp & 3) * 2 + (g & 1)) ^ (h & 7);
            str1(sp + G_H3 + (j * 2 + (warp >> 2)) * 8192 + q * 4096 + h * 128 + chunk * 16 + (g >> 1) * 4, w2 ^ 0xFFFF0000u);
        }
        if (lane == 0) mbar_arrive(bars + B_UK * 8);
    }
    TS0(5);
    {
        const unsigned char* src[5];
#pragma unroll
        for (int i = 0; i < 5; i++) src[i] = sp + pick(G_H3 + (i < 4 ? rank * 4 + i : (rank ^ 1) * 4 + 3) * 8192 + tid * 16, beta);
        uint4 v[5];
        wait_until(t_start, p.tm[T_H3]);
#pragma unroll
        for (int i = 0; i < 5; i++) v[i] = ldr4(src[i]);
        int it = 0;
#pragma unroll 1
        while (true) {
            bool ok = true;
#pragma unroll
            for (int i = 0; i < 5; i++) if (!nz4(v[i])) { v[i] = ldr4(src[i]); ok = false; }
            if (__all_sync(~0u, ok)) break;
            SPIN_CHECK(it);
        }
        TS0(31);
#pragma unroll
        for (int i = 0; i < 5; i++)
            sts4(sb + S_QABS + i * 4096 + tid * 16, v[i].x ^ 0xFFFF0000u, v[i].y ^ 0xFFFF0000u, v[i].z ^ 0xFFFF0000u, v[i].w ^ 0xFFFF0000u);
        fence_async();
        bar_sync(2, 256);
    }
    TS0(6);
    if (wg) {
        uint32_t bw; int it = 0;
#pragma unroll 1
        do { bw = ldr1(sp + G_H4 + 65536 + 128 + ((tid & 127) >> 1) * 131072 + (tid & 1) * 256); SPIN_CHECK(it); } while (__any_sync(~0u, (bw ^ tg) & 1));
        const uint32_t mb = __ballot_sync(~0u, bw & 2), mt = __ballot_sync(~0u, bw & 4);
        if (lane == 0) sts2(sb + S_B4 + wq * 8, mb, mt);
    }
    mbar_wait(bars + B_BETA4 * 8);
    const uint32_t rec = lds1(sb + S_EP + 8), tg4w = rec >> 2 & 1;
    unsigned char* const h4dst = sp + pick(G_H4 + pair * 131072 + spread(q * 2048 + wq * 256 + rank * 128 + g * 8), rec >> 1);
    {
        float s[16];
#pragma unroll
        for (int i = 0; i < 16; i++) s[i] = 0.f;
        const uint32_t xo = (wg ? S_XBUF1 : S_XBUF0) + (tid & 127) * 16;
#pragma unroll 1
        for (int cg = 0; cg < 4 - wg; cg++) {
            mbar_wait(bars + (C_CKV + wg * 4 + cg) * 8);
            const uint64_t da = mkdesc(sb + S_CKV + (wg * 4 + cg) * 8192), db = mkdesc(sb + S_QABS + cg * 4096);
            wg_fence();
#pragma unroll
            for (int k = 0; k < 4; k++) wgmma_n32<0>(s, da + k * 2, db + k * 2, 1);
            wg_commit();
        }
        wg_wait<0>();
        reg_fence16(s);
        TS0(64);
        {
            uint32_t ra, rb;
            asm("mapa.shared::cluster.u32 %0, %1, %2;" : "=r"(ra) : "r"(sb + xo), "r"(rank ^ 1));
            asm("mapa.shared::cluster.u32 %0, %1, %2;" : "=r"(rb) : "r"(bars + (B_X + wg) * 8), "r"(rank ^ 1));
#pragma unroll
            for (int i = 0; i < 4; i++)
                asm volatile("st.async.weak.shared::cluster.mbarrier::complete_tx::bytes.v4.f32 [%0], {%1,%2,%3,%4}, [%5];"
                             ::"r"(ra + i * 2048), "f"(s[4 * i]), "f"(s[4 * i + 1]), "f"(s[4 * i + 2]), "f"(s[4 * i + 3]), "r"(rb) : "memory");
        }
        if (wg) {
#pragma unroll 1
            for (int c = 0; c < 2; c++) {
                mbar_wait(bars + (C_X - 1 + c) * 8);
                const uint64_t da = mkdesc(sb + (c ? S_XCH : S_CKV + 7 * 8192)), db = mkdesc(sb + S_QABS + (3 + c) * 4096);
                wg_fence();
#pragma unroll
                for (int k = 0; k < 4; k++) wgmma_n32<0>(s, da + k * 2, db + k * 2, 1);
                wg_commit();
            }
        }
        mbar_wait_cluster(bars + (B_X + wg) * 8);
        float4 xs[4];
#pragma unroll
        for (int i = 0; i < 4; i++) xs[i] = lds4f(sb + xo + i * 2048);
        wg_wait<0>();
        reg_fence16(s);
        TS4(7); TS0(65);
#pragma unroll
        for (int i = 0; i < 4; i++) { s[4 * i] += xs[i].x; s[4 * i + 1] += xs[i].y; s[4 * i + 2] += xs[i].z; s[4 * i + 3] += xs[i].w; }
        const bool b2 = lane & 16, b1 = lane & 8, b0 = lane & 4;
        {
            float v[8];
#pragma unroll
            for (int i = 0; i < 4; i++) { v[2 * i] = fmaxf(s[4 * i], s[4 * i + 2]); v[2 * i + 1] = fmaxf(s[4 * i + 1], s[4 * i + 3]); }
            float u[4];
#pragma unroll
            for (int k = 0; k < 4; k++) u[k] = fmaxf(b2 ? v[k + 4] : v[k], __shfl_xor_sync(~0u, b2 ? v[k] : v[k + 4], 16));
            float t[2];
#pragma unroll
            for (int k = 0; k < 2; k++) t[k] = fmaxf(b1 ? u[k + 2] : u[k], __shfl_xor_sync(~0u, b1 ? u[k] : u[k + 2], 8));
            const uint32_t r = ordf(__float_as_uint(fmaxf(b0 ? t[1] : t[0], __shfl_xor_sync(~0u, b0 ? t[0] : t[1], 4))));
            const uint32_t a = sb + S_MAX + (8 * (g >> 1) + 2 * q + (g & 1)) * 4;
            red_max(a + 128, r);
            if (wg == 0) red_max(a, r);
        }
        if (wg == 0) { bar_arrive(4, 256); bar_sync(3, 128); } else { bar_arrive(7, 256); bar_sync(4, 256); }
        TS4(66);
        uint32_t pk[8];
#pragma unroll
        for (int i = 0; i < 4; i++) {
            const float2 mm = lds2f(sb + S_MAX + wg * 128 + (8 * i + 2 * q) * 4);
            const float m0 = u2f(ordf(__float_as_uint(mm.x))), m1 = u2f(ordf(__float_as_uint(mm.y)));
            pk[2 * i] = packbf(ex2(s[4 * i] - m0), ex2(s[4 * i + 1] - m1));
            pk[2 * i + 1] = packbf(ex2(s[4 * i + 2] - m0), ex2(s[4 * i + 3] - m1));
        }
        {
            const int t = lane >> 3, r8 = lane & 7;
            const uint32_t a = sb + S_P + wg * 4096 + ((t >> 1) * 8 + r8) * 128 + (((2 * wq + (t & 1)) ^ r8) << 4);
            stsm4t(a, pk[0], pk[1], pk[2], pk[3]);
            stsm4t(a + 2048, pk[4], pk[5], pk[6], pk[7]);
        }
        fence_async();
        TS4(67); TS0(68);
        if (wg) {
            bar_arrive(5, 256);
            if (warp == 4) {
                str1(sp + G_ML + spread(pair * 256 + lane * 4) + rank * 4096, tagf(u2f(ordf(lds1(sb + S_MAX + 128 + lane * 4))), tg));
                if (lane == 0) mbar_arrive(bars + B_QK * 8);
            }
        } else {
            float o0[16], o1[16], o2[16], o3[16], ol[16];
            const uint64_t d1 = mkdesc(sb + S_ONES) & ~(0x3FFFull << 32);
            const uint64_t db = mkdesc(sb + S_P), da = mkdesc(sb + S_CKV);
            bar_sync(3, 128);
            wg_fence();
#pragma unroll
            for (int k = 0; k < 4; k++) {
                wgmma_n32<1>(o0, da + k * 128, db + k * 2, k);
                wgmma_n32<1>(o1, da + 512 + k * 128, db + k * 2, k);
                wgmma_n32<1>(o2, da + 1024 + k * 128, db + k * 2, k);
                wgmma_n32<1>(o3, da + 1536 + k * 128, db + k * 2, k);
                wgmma_n32<0>(ol, d1, db + k * 2, k);
            }
            wg_commit();
            wg_wait<0>();
            reg_fence16(o0); reg_fence16(o1); reg_fence16(o2); reg_fence16(o3); reg_fence16(ol);
            TS0(23);
            bar_sync(7, 256);
            {
                const float al = ex2(u2f(ordf(lds1(sb + S_MAX + lane * 4))) - u2f(ordf(lds1(sb + S_MAX + 128 + lane * 4))));
#pragma unroll
                for (int i = 0; i < 4; i++) {
                    const float a0 = __shfl_sync(~0u, al, 8 * i + 2 * q), a1 = __shfl_sync(~0u, al, 8 * i + 2 * q + 1);
                    o0[4 * i] *= a0; o0[4 * i + 1] *= a1; o0[4 * i + 2] *= a0; o0[4 * i + 3] *= a1;
                    o1[4 * i] *= a0; o1[4 * i + 1] *= a1; o1[4 * i + 2] *= a0; o1[4 * i + 3] *= a1;
                    o2[4 * i] *= a0; o2[4 * i + 1] *= a1; o2[4 * i + 2] *= a0; o2[4 * i + 3] *= a1;
                    o3[4 * i] *= a0; o3[4 * i + 1] *= a1; o3[4 * i + 2] *= a0; o3[4 * i + 3] *= a1;
                    ol[4 * i] *= a0; ol[4 * i + 1] *= a1; ol[4 * i + 2] *= a0; ol[4 * i + 3] *= a1;
                }
            }
            unsigned char* ldst = sp + G_ML + spread(pair * 256 + 128 + wq * 32 + q * 8) + rank * 4096;
            PIN(ldst);
            TS0(81);
            bar_sync(5, 256);
            wg_fence();
#pragma unroll
            for (int k = 0; k < 4; k++) {
                wgmma_n32<0>(ol, d1, db + 256 + k * 2, 1);
                wgmma_n32<1>(o0, da + 2048 + k * 128, db + 256 + k * 2, 1);
                wgmma_n32<1>(o1, da + 2048 + 512 + k * 128, db + 256 + k * 2, 1);
            }
            wg_commit();
            wg_wait<0>();
            reg_fence16(ol); reg_fence16(o0); reg_fence16(o1);
            TS0(24);
            wg_fence();
#pragma unroll
            for (int k = 0; k < 4; k++) {
                wgmma_n32<1>(o2, da + 2048 + 1024 + k * 128, db + 256 + k * 2, 1);
                wgmma_n32<1>(o3, da + 2048 + 1536 + k * 128, db + 256 + k * 2, 1);
            }
            wg_commit();
            {
                const float l0 = (wq & 2) ? ((wq & 1) ? ol[12] : ol[8]) : ((wq & 1) ? ol[4] : ol[0]);
                const float l1 = (wq & 2) ? ((wq & 1) ? ol[13] : ol[9]) : ((wq & 1) ? ol[5] : ol[1]);
                if (g == 0) str2(ldst, tagf(l0, tg), tagf(l1, tg));
            }
#define O_STORE(A, B, OFF) _Pragma("unroll") for (int i = 0; i < 4; i++) _Pragma("unroll") for (int e = 0; e < 2; e++) { \
                const float f0 = u2f((__float_as_uint(A[4 * i + e]) + 0x10000u) & 0xFFFE0000u); \
                str64(h4dst + (OFF) + i * 16384 + e * 1024, packbf(f0, A[4 * i + 2 + e]) | tg4w, packbf(B[4 * i + e], B[4 * i + 2 + e])); }
            TS0(8);
            O_STORE(o0, o1, 0);
            __syncwarp();
            wg_wait<0>();
            reg_fence16(o2); reg_fence16(o3);
            O_STORE(o2, o3, 64);
        }
    }
    TS0(9);
    const uint32_t t_o = clk32();
    uint32_t af[8][4];
    {
        const int sg = tid >> 4, u = tid & 15;
        uint32_t a0;
        {
            const int m = lane >> 3, r8 = lane & 7;
            const int row = (m >> 1) * 16 + (r8 >> 1) * 2 + (r8 & 1) * 8;
            a0 = sb + S_WUV + wg * 4096 + row * 128 + (((wq * 2 + (m & 1)) ^ (row & 7)) << 4);
        }
        const unsigned char* src[4];
        uint32_t tg4[4];
#pragma unroll
        for (int i = 0; i < 4; i++) {
            const float2 m = lds2f(sb + S_B4 + i * 8);
            src[i] = sp + pick(G_H4 + (sg + 16 * i) * 131072 + spread(b * 256 + u * 16), __float_as_uint(m.x) >> (sg * 2 + (u >> 3)));
            tg4[i] = __float_as_uint(m.y) >> (sg * 2 + (u >> 3));
        }
        uint4 v[4];
        uint32_t have = 0;
        int it = 0;
        unsigned char* d5 = sp + G_H5 + spread(b * 512 + warp * 64 + (q & 1) * 32 + g * 4) + (q >> 1) * 4096;
        PIN(d5);
        wait_until(t_o, p.tm[D_H4]);
        wait_until(t_start, p.tm[T_H4]);
#pragma unroll
        for (int i = 0; i < 4; i++) v[i] = ldr64x2(src[i]);
        TS0(10);
#define LOAD_UV(now) _Pragma("unroll") for (int i = 0; i < 4; i++) \
            if ((now) >> i & 1) { ldsm4t(a0 + i * 8192, af[2 * i]); ldsm4t((a0 + i * 8192 + 128) ^ 16, af[2 * i + 1]); }
        have = mbar_mask4(bars + C_WUV * 8);
        LOAD_UV(have);
        mbar_wait(bars + B_W * 8);
        float wt[4];
#pragma unroll
        for (int i = 0; i < 4; i++) wt[i] = lds1f(sb + S_ML + (sg + 16 * i) * 4);
#pragma unroll 1
        while (__any_sync(~0u, (or3(xo2(v[0].x, v[0].z, tg4[0]), xo2(v[1].x, v[1].z, tg4[1]), xo2(v[2].x, v[2].z, tg4[2])) | xo2(v[3].x, v[3].z, tg4[3])) & 1)) {
#pragma unroll
            for (int i = 0; i < 4; i++) if (xo2(v[i].x, v[i].z, tg4[i]) & 1) v[i] = ldr64x2(src[i]);
            SPIN_CHECK(it);
        }
        float acc[8] = {0.f, 0.f, 0.f, 0.f, 0.f, 0.f, 0.f, 0.f};
#pragma unroll
        for (int i = 0; i < 4; i++) {
            const uint32_t w[4] = {v[i].x & ~1u, v[i].y, v[i].z & ~1u, v[i].w};
#pragma unroll
            for (int k = 0; k < 4; k++) {
                acc[2 * k] = fmaf(wt[i], bflo(w[k]), acc[2 * k]);
                acc[2 * k + 1] = fmaf(wt[i], bfhi(w[k]), acc[2 * k + 1]);
            }
        }
        TS0(25);
        {
            const bool up = lane & 16;
            float r[4];
#pragma unroll
            for (int k = 0; k < 4; k++) r[k] = ((up ? acc[k + 4] : acc[k]) + __shfl_xor_sync(~0u, up ? acc[k] : acc[k + 4], 16));
            sts2(sb + S_RED + warp * 320 + u * 16 + (up ? 8 : 0), packbf(r[0], r[1]), packbf(r[2], r[3]));
        }
        bar_sync(2, 256);
        uint4 bq[4];
#pragma unroll
        for (int i = 0; i < 4; i++) bq[i] = lds4(sb + S_RED + g * 320 + i * 64 + q * 16);
        if (have != 15) { mbar_wait4(bars + C_WUV * 8); LOAD_UV(~have); }
        float d[4][4];
#pragma unroll
        for (int i = 0; i < 4; i++) {
            d[i][0] = d[i][1] = d[i][2] = d[i][3] = 0.f;
            mma16816(d[i], af[2 * i], bq[i].x, bq[i].y);
            mma16816(d[i], af[2 * i + 1], bq[i].z, bq[i].w);
        }
        const float r0 = ((d[0][0] + d[0][1]) + (d[1][0] + d[1][1])) + ((d[2][0] + d[2][1]) + (d[3][0] + d[3][1]));
        const float r1 = ((d[0][2] + d[0][3]) + (d[1][2] + d[1][3])) + ((d[2][2] + d[2][3]) + (d[3][2] + d[3][3]));
        float r = ((q & 1) ? r1 : r0) + __shfl_xor_sync(~0u, (q & 1) ? r0 : r1, 1);
        r += __shfl_xor_sync(~0u, r, 2);
        str1(d5, tagf(r, tg));
    }
    const uint32_t t_e = clk32();
    TS0(12);
    const unsigned char* sm[4];
    uint2 mm[6];
#pragma unroll
    for (int i = 0; i < 4; i++) sm[i] = sp + pick(G_MOD2 + i * 8192 + tid * 8, beta);
#define LOAD_MM() do { mm[0] = ldr2(sm[0]); mm[1] = ldr2(sm[0] + 2048); mm[2] = ldr2(sm[1]); mm[3] = ldr2(sm[2]); mm[4] = ldr2(sm[2] + 2048); mm[5] = ldr2(sm[3]); } while (0)
#define BAD_MM() or3(or3(bad2(mm[0], tg), bad2(mm[1], tg), bad2(mm[2], tg)), or3(bad2(mm[3], tg), bad2(mm[4], tg), bad2(mm[5], tg)), 0)
    {
        const int m = lane >> 3, r8 = lane & 7;
        const uint32_t a0 = sb + S_WO + (warp >> 1) * 2048 + ((m >> 1) * 8 + r8) * 64 + ((((warp & 1) * 2 + (m & 1)) ^ (r8 >> 1)) << 4);
        const unsigned char* src = sp + pick(G_H5 + spread(((b >> 4) * 4 + (warp >> 1)) * 2048 + (tid & 63) * 8), beta);
        uint2 c0, c1, c2, c3; int it = 0;
        uint32_t have = 0;
        unsigned char* d6 = sp + G_H6 + spread(b * 128 + lane * 4) + (warp & 1) * 4096;
        PIN(d6);
        wait_until(t_e, p.tm[D_H5]);
#pragma unroll 1
        do {
            c0 = ldr2(src); c1 = ldr2(src + 512); c2 = ldr2(src + 1024); c3 = ldr2(src + 1536);
            const uint32_t now = mbar_mask4(bars + C_WO * 8) & ~have;
#pragma unroll
            for (int i = 0; i < 4; i++)
                if (now >> i & 1) { ldsm4t(a0 + i * 8192, af[2 * i]); ldsm4t(a0 + i * 8192 + 1024, af[2 * i + 1]); }
            have |= now;
            SPIN_CHECK(it);
        } while (__any_sync(~0u, or3(or3(bad2(c0, tg), bad2(c1, tg), bad2(c2, tg)), bad2(c3, tg), 0) & 1));
        uint32_t hi, lo;
        split2((u2f(c0.x) + u2f(c1.x)) + (u2f(c2.x) + u2f(c3.x)), (u2f(c0.y) + u2f(c1.y)) + (u2f(c2.y) + u2f(c3.y)), hi, lo);
        const uint32_t a = sb + S_FVEC + (tid >> 4) * 128 + vpos((tid & 15) * 2);
        sts1(a, hi); sts1(a + 64, lo);
        TS0(14);
        bar_sync(2, 256);
        if (b < NFFN) LOAD_MM();
        uint4 bq[4];
#pragma unroll
        for (int i = 0; i < 4; i++) bq[i] = lds4(sb + S_FVEC + (i * 4 + (warp >> 1)) * 128 + vlane);
        if (have != 15) {
#pragma unroll
            for (int i = 0; i < 4; i++)
                if (!(have >> i & 1)) {
                    mbar_wait(bars + (C_WO + i) * 8);
                    ldsm4t(a0 + i * 8192, af[2 * i]); ldsm4t(a0 + i * 8192 + 1024, af[2 * i + 1]);
                }
        }
        float d[4][4];
#pragma unroll
        for (int i = 0; i < 4; i++) {
            d[i][0] = d[i][1] = d[i][2] = d[i][3] = 0.f;
            mma16816(d[i], af[2 * i], bq[i].x, bq[i].y);
            mma16816(d[i], af[2 * i + 1], bq[i].z, bq[i].w);
        }
        TS0(15);
        if (q == 0) {
            const uint32_t o = sb + S_R16 + ((warp & 1) * 16 + g) * 16 + (warp >> 1) * 4;
            sts1f(o, ((d[0][0] + d[0][1]) + (d[1][0] + d[1][1])) + ((d[2][0] + d[2][1]) + (d[3][0] + d[3][1])));
            sts1f(o + 128, ((d[0][2] + d[0][3]) + (d[1][2] + d[1][3])) + ((d[2][2] + d[2][3]) + (d[3][2] + d[3][3])));
        }
        bar_sync(2, 256);
        if (tid < 64) {
            const float4 u = lds4f(sb + S_R16 + lane * 16);
            str1(d6, tagf((u.x + u.y) + (u.z + u.w), tg));
        }
        if (tid == 64) mbar_arrive(bars + B_F * 8);
        if (tid >= 224) str4(sp + G_H3 + (j * 2 + ((tid >> 3) & 1)) * 8192 + (tid & 16) * 256 + h * 128 + (tid & 7) * 16, 0, 0, 0, 0);
    }
    const uint32_t t_f = clk32();
    TS0(26);
    if (b < NFFN) {
        const uint32_t ga_ = sb + S_GVEC + (warp * 2 + (lane >> 4)) * 512 + vpos((lane & 15) * 2);
        TS0(16);
        const int m = lane >> 3, r8 = lane & 7;
        const uint32_t a0 = sb + S_W1 + warp * 2048 + ((m >> 1) * 8 + r8) * 32 + (((m & 1) ^ (r8 >> 2)) << 4);
        bool have1 = false;
        unsigned char* d7 = sp + G_H7 + spread(b * 2048 + tid * 8);
        PIN(d7);
        float x20, x21;
        {
            const unsigned char* so[4];
#pragma unroll
            for (int i = 0; i < 4; i++) so[i] = sp + pick(G_H6 + i * 8192 + tid * 8, beta);
            uint2 c[8]; int it = 0;
            float g0, g1;
#define STAGE_MM() do { \
                g0 = 1.f + (u2f(mm[2].x) + u2f(mm[5].x)); g1 = 1.f + (u2f(mm[2].y) + u2f(mm[5].y)); \
                uint32_t hi, lo; \
                split2(g0, g1, hi, lo); sts1(ga_ + 128, hi); sts1(ga_ + 192, lo); \
                split2(u2f(mm[1].x) + u2f(mm[4].x), u2f(mm[1].y) + u2f(mm[4].y), hi, lo); sts1(ga_ + 256, hi); sts1(ga_ + 320, lo); } while (0)
#pragma unroll 1
            while (BAD_MM() & 1) { LOAD_MM(); SPIN_CHECK(it); }
            STAGE_MM();
            have1 = mbar_mask4(bars + C_W1 * 8) >> wg & 1;
            if (have1) {
#pragma unroll
                for (int i = 0; i < 4; i++) ldsm4t(a0 + i * 512, af[i]);
            }
            wait_until(t_f, p.tm[D_H6]);
#pragma unroll 1
            while (true) {
#pragma unroll
                for (int i = 0; i < 8; i++) c[i] = ldr2(so[i >> 1] + (i & 1) * 2048);
                uint32_t bc = 0;
                bc = or3(or3(bad2(c[0], tg), bad2(c[1], tg), bad2(c[2], tg)), or3(bad2(c[3], tg), bad2(c[4], tg), bad2(c[5], tg)),
                         or3(bad2(c[6], tg), bad2(c[7], tg), bc));
                if (!__any_sync(~0u, bc & 1)) break;
                SPIN_CHECK(it);
            }
            x20 = fmaf(u2f(mm[0].x) + u2f(mm[3].x),
                       ((u2f(c[0].x) + u2f(c[1].x)) + (u2f(c[2].x) + u2f(c[3].x))) + ((u2f(c[4].x) + u2f(c[5].x)) + (u2f(c[6].x) + u2f(c[7].x))), bflo(xw2));
            x21 = fmaf(u2f(mm[0].y) + u2f(mm[3].y),
                       ((u2f(c[0].y) + u2f(c[1].y)) + (u2f(c[2].y) + u2f(c[3].y))) + ((u2f(c[4].y) + u2f(c[5].y)) + (u2f(c[6].y) + u2f(c[7].y))), bfhi(xw2));
            uint32_t hi, lo;
            split2(x20 * g0, x21 * g1, hi, lo); sts1(ga_, hi); sts1(ga_ + 64, lo);
            split2(x20, x21, hi, lo); sts1(ga_ + 384, hi); sts1(ga_ + 448, lo);
        }
        TS0(17);
        __syncwarp();
        const uint32_t va = sb + S_GVEC + warp * 1024 + g * 64 + q * 16;
        const uint4 bq0 = lds4(va), bq1 = lds4(va + 512);
        if (!have1) {
            mbar_wait(bars + (C_W1 + wg) * 8);
#pragma unroll
            for (int i = 0; i < 4; i++) ldsm4t(a0 + i * 512, af[i]);
        }
        float d0[4] = {0.f, 0.f, 0.f, 0.f}, d1[4] = {0.f, 0.f, 0.f, 0.f}, d2[4] = {0.f, 0.f, 0.f, 0.f}, d3[4] = {0.f, 0.f, 0.f, 0.f};
        mma16816(d0, af[0], bq0.x, bq0.y); mma16816(d1, af[1], bq0.z, bq0.w);
        mma16816(d2, af[2], bq1.x, bq1.y); mma16816(d3, af[3], bq1.z, bq1.w);
        float e0[4] = {0.f, 0.f, 0.f, 0.f}, e1[4] = {0.f, 0.f, 0.f, 0.f};
        {
            const uint32_t one = 0x3F803F80u;
            const uint32_t t0[4] = {bq0.x, one, bq0.y, one}, t1[4] = {bq0.z, one, bq0.w, one};
            const uint32_t t2[4] = {bq1.x, one, bq1.y, one}, t3[4] = {bq1.z, one, bq1.w, one};
            mma16816(e0, t0, bq0.x, bq0.y); mma16816(e1, t1, bq0.z, bq0.w);
            mma16816(e0, t2, bq1.x, bq1.y); mma16816(e1, t3, bq1.z, bq1.w);
        }
        {
            const bool st = q == 3;
            const float lo_ = fsel(st, (e0[0] + e0[1]) + (e1[0] + e1[1]), ((d0[0] + d0[1]) + (d1[0] + d1[1])) + ((d2[0] + d2[1]) + (d3[0] + d3[1])));
            const float hi_ = fsel(st, (e0[2] + e0[3]) + (e1[2] + e1[3]), ((d0[2] + d0[3]) + (d1[2] + d1[3])) + ((d2[2] + d2[3]) + (d3[2] + d3[3])));
            sts1f(sb + S_RED + q * 512 + g * 32 + warp * 4, lo_);
            sts1f(sb + S_RED + q * 512 + (g + 8) * 32 + warp * 4, hi_);
        }
        TS0(18);
        bar_arrive(9, 288);
        uint32_t w2r[16];
        mbar_wait(bars + C_W2 * 8); mbar_wait(bars + (C_W2 + 1) * 8);
#pragma unroll
        for (int r = 0; r < 16; r++) w2r[r] = lds1(sb + S_W2 + r * 1024 + tid * 4);
        float w2f[32];
#pragma unroll
        for (int r = 0; r < 16; r++) { w2f[2 * r] = bflo(w2r[r]); w2f[2 * r + 1] = bfhi(w2r[r]); }
        bar_sync(10, 288);
        float y0a = 0.f, y0b = 0.f, y1a = 0.f, y1b = 0.f;
#pragma unroll
        for (int r = 0; r < 16; r += 4) {
            const float4 f = lds4f(sb + S_STAT + r * 4);
            y0a = fmaf(f.x, w2f[2 * r], y0a); y1a = fmaf(f.x, w2f[2 * r + 1], y1a);
            y0b = fmaf(f.y, w2f[2 * r + 2], y0b); y1b = fmaf(f.y, w2f[2 * r + 3], y1b);
            y0a = fmaf(f.z, w2f[2 * r + 4], y0a); y1a = fmaf(f.z, w2f[2 * r + 5], y1a);
            y0b = fmaf(f.w, w2f[2 * r + 6], y0b); y1b = fmaf(f.w, w2f[2 * r + 7], y1b);
        }
        const uint32_t w0 = tagf(y0a + y0b, tg), w1 = tagf(y1a + y1b, tg);
        str2(d7, w0, w1); str2(d7 + 4096, w0, w1);
        TS0(19);
    }
}

typedef CUresult (*EncodeFn)(CUtensorMap*, CUtensorMapDataType, cuuint32_t, void*, const cuuint64_t*, const cuuint64_t*,
                             const cuuint32_t*, const cuuint32_t*, CUtensorMapInterleave, CUtensorMapSwizzle,
                             CUtensorMapL2promotion, CUtensorMapFloatOOBfill);

CUtensorMapL2promotion g_prom_narrow = CU_TENSOR_MAP_L2_PROMOTION_L2_128B;
void make_map(EncodeFn enc, CUtensorMap* m, const void* ptr, uint64_t d0, uint64_t d1, uint64_t d2, uint64_t d3,
              uint64_t s1, uint64_t s2, uint64_t s3, uint32_t b0, uint32_t b1, uint32_t b2, uint32_t b3, CUtensorMapSwizzle sw) {
    const auto prom = b0 == 16 ? g_prom_narrow : CU_TENSOR_MAP_L2_PROMOTION_L2_128B;
    cuuint64_t dims[4] = {d0, d1, d2, d3};
    cuuint64_t st[3] = {s1, s2, s3};
    cuuint32_t box[4] = {b0, b1, b2, b3};
    cuuint32_t es[4] = {1, 1, 1, 1};
    enc(m, CU_TENSOR_MAP_DATA_TYPE_BFLOAT16, 4, const_cast<void*>(ptr), dims, st, box, es, CU_TENSOR_MAP_INTERLEAVE_NONE, sw,
        prom, CU_TENSOR_MAP_FLOAT_OOB_FILL_NONE);
}

uint16_t g_tm[NTM] = {3860,7030,14800,330,490,770,870,420};
uint16_t g_sched[32] = {0,1120,1714,2308,2902,3496,4090,4684,5278,5872,6466,7060,7654,8248,8842,9436,
                        10030,10130,10450,10970,11280,12650,13590,14810,14830,15350,16590,17140,17960,18710,18790,19370};

}

extern "C" void kernel_launch(void* const* d_in, const int* in_sizes, int n_in, void* d_out, int out_size) {
    (void)in_sizes; (void)n_in; (void)out_size;
    static EncodeFn enc = nullptr;
    static unsigned char* scratch = nullptr;
    if (!enc) {
        cudaGetSymbolAddress((void**)&scratch, g_scratch);
        scratch = (unsigned char*)(((uintptr_t)scratch + (2 << 20) - 1) & ~(uintptr_t)((2 << 20) - 1));
        void* fn = nullptr;
        cudaDriverEntryPointQueryResult qr;
        cudaGetDriverEntryPoint("cuTensorMapEncodeTiled", &fn, cudaEnableDefault, &qr);
        enc = (EncodeFn)fn;
        cudaFuncSetAttribute(fused_decode_kernel, cudaFuncAttributeMaxDynamicSharedMemorySize, SMEM_BYTES);
    }
    Params p;
    const auto S128 = CU_TENSOR_MAP_SWIZZLE_128B, S32 = CU_TENSOR_MAP_SWIZZLE_32B, S64 = CU_TENSOR_MAP_SWIZZLE_64B, S0 = CU_TENSOR_MAP_SWIZZLE_NONE;
    make_map(enc, &p.m[0], d_in[12], 3072, 512, 1, 1, 6144, 6144 * 512, 6144 * 512, 16, 256, 1, 1, S32);
    make_map(enc, &p.m[1], d_in[2], 64, 512, 64, 1, 8192, 128, 8192 * 512, 64, 32, 2, 1, S128);
    make_map(enc, &p.m[2], d_in[3], 64, 512, 64, 1, 8192, 128, 8192 * 512, 64, 32, 2, 1, S128);
    make_map(enc, &p.m[3], d_in[1], 64, 8192, 8, 1, 1024, 128, 1024 * 8192, 64, 64, 1, 1, S128);
    make_map(enc, &p.m[4], d_in[4], 64, 64, 8, 64, 8192, 8192 * 64, 128, 64, 16, 2, 2, S128);
    make_map(enc, &p.m[5], d_in[5], 512, 4096, 1, 1, 1024, 1024 * 4096, 1024 * 4096, 32, 128, 1, 1, S64);
    make_map(enc, &p.m[8], d_in[12], 3072, 512, 1, 1, 6144, 6144 * 512, 6144 * 512, 32, 128, 1, 1, S64);
    make_map(enc, &p.m[6], d_in[7], 1376, 512, 1, 1, 2752, 2752 * 512, 2752 * 512, 16, 256, 1, 1, S32);
    make_map(enc, &p.m[7], d_in[9], 256, 2752, 1, 1, 512, 512 * 2752, 512 * 2752, 256, 16, 1, 1, S0);
    p.x = (const __nv_bfloat16*)d_in[0];
    p.c = (const __nv_bfloat16*)d_in[11];
    p.b1 = (const __nv_bfloat16*)d_in[8];
    p.b2 = (const __nv_bfloat16*)d_in[10];
    p.out = (__nv_bfloat16*)d_out;
    p.s = scratch;
    for (int i = 0; i < NTM; i++) p.tm[i] = g_tm[i];
    for (int i = 0; i < 32; i++) p.sched[i] = g_sched[i];
    fused_decode_kernel<<<NCTA, NTHR, SMEM_BYTES, cudaStreamPerThread>>>(p);
}
```

```cpp
#include <cuda_runtime.h>
#include <cuda_bf16.h>
#include <cuda.h>
#include <stdint.h>

namespace {

constexpr int NCTA   = 128;
constexpr int NFFN   = 86;
constexpr int NCHUNK = 33;
constexpr int NTHR   = 384;

constexpr int C_MOD1 = 0, C_WQ = 1, C_WUK = 5, C_CKV = 9, C_T1 = 15, C_WUV = 19, C_W1 = 29, C_W2 = 31;
constexpr int C_MOD2 = 23, C_WO = 25;

constexpr int S_WQ   = 0;
constexpr int S_WUK  = 32768;
constexpr int S_CKV  = 65536;
constexpr int S_WUV  = 131072;
constexpr int S_WO   = 163840;
constexpr int S_MOD2 = 196608;
constexpr int S_MOD1 = 212992;
constexpr int S_SC   = 221184;
constexpr int S_RED  = 223232;
constexpr int S_VEC  = 227328;
constexpr int S_R16  = 227840;
constexpr int S_MAX  = 228352;
constexpr int S_ONES = 229376;
constexpr int S_ML   = 230400;
constexpr int S_X2   = 230400 + 384;
constexpr int S_STAT = 230912;
constexpr int S_BAR  = 230976;
constexpr int S_EP   = 231312;
constexpr int S_B4   = 230912;
constexpr int S_TS   = 231328;
constexpr int S_END  = 231712;
constexpr int S_QABS = S_WQ, S_XBUF1 = S_WQ + 24576, S_XBUF0 = S_MOD1, S_XCH = S_WUK, S_GVEC = S_WQ, S_FVEC = S_WQ + 8192;
constexpr int S_W1 = S_WUK, S_W2 = S_WUK + 16384, S_P = S_MOD1;
constexpr int B_UK = 33, B_QK = 34, B_X = 35, B_F = 37, B_BETA = 38, B_BETA4 = 39, B_W = 40, B_O = 41, NBAR = 42;
constexpr int SMEM_BYTES = S_END;

constexpr int WIN = 5;
enum { T_H1 = 0, T_H3, T_H4, D_H5, D_H6, D_H7, D_H4, A_H4, NTM = 8 };

constexpr uint32_t G_H1 = 0;
constexpr uint32_t G_H6 = 192 << 10;
constexpr uint32_t G_MOD2 = 16 << 10;
constexpr uint32_t G_ML = 48 << 10;
constexpr uint32_t G_PROBE = 88 << 10;
constexpr uint32_t G_H3 = 128 << 10;
constexpr uint32_t G_H2 = 256 << 10;
constexpr uint32_t G_H5 = 384 << 10;
constexpr uint32_t G_H7 = 512 << 10;
constexpr uint32_t G_EPOCH = 1 << 20;
constexpr uint32_t G_TS = (1 << 20) + 4096;
constexpr uint32_t G_H4 = 2 << 20;
constexpr uint32_t G_BYTES = 10 << 20;
__device__ __align__(256) unsigned char g_scratch[G_BYTES + (2 << 20)];
__device__ __forceinline__ uint32_t spread(uint32_t o) { return o + (o & ~4095u); }
__device__ __forceinline__ uint32_t pick(uint32_t po, uint32_t beta) {
    return po + (((beta ^ __popc(po & 0xB2000u)) & 1u) << 12);
}
#define TS(i) do {} while (0)
#define TS0(i) do {} while (0)
#define TS4(i) do {} while (0)

struct Params {
    const __nv_bfloat16* x;
    const __nv_bfloat16* c;
    const __nv_bfloat16* b1;
    const __nv_bfloat16* b2;
    __nv_bfloat16* out;
    unsigned char* s;
    uint16_t tm[NTM];
    uint16_t sched[34];
    CUtensorMap m[9];
};

constexpr uint64_t POL_FIRST = 0x12F0000000000000ull, POL_NORMAL = 0x16F0000000000000ull;
constexpr int SPIN_MAX = 1 << 21;

__device__ __forceinline__ void mbar_init(uint32_t bar, uint32_t cnt) {
    asm volatile("mbarrier.init.shared::cta.b64 [%0], %1;" ::"r"(bar), "r"(cnt) : "memory");
}
__device__ __forceinline__ void mbar_expect_tx(uint32_t bar, uint32_t bytes) {
    asm volatile("mbarrier.arrive.expect_tx.shared::cta.b64 _, [%0], %1;" ::"r"(bar), "r"(bytes) : "memory");
}
__device__ __forceinline__ void mbar_arrive(uint32_t bar) {
    asm volatile("mbarrier.arrive.shared::cta.b64 _, [%0];" ::"r"(bar) : "memory");
}
__device__ __forceinline__ void mbar_wait(uint32_t bar) {
    asm volatile("{\n.reg .pred p;\nW:\nmbarrier.try_wait.parity.shared::cta.b64 p, [%0], 0;\n@!p bra W;\n}" ::"r"(bar) : "memory");
}
__device__ __forceinline__ void mbar_wait2(uint32_t bar) {
    asm volatile("{\n.reg .pred p, q;\nW:\n"
                 "mbarrier.try_wait.parity.shared::cta.b64 p, [%0], 0;\n"
                 "mbarrier.try_wait.parity.shared::cta.b64 q, [%0+8], 0;\n"
                 "and.pred p, p, q;\n@!p bra W;\n}" ::"r"(bar) : "memory");
}
__device__ __forceinline__ void mbar_wait4(uint32_t bar) {
    asm volatile("{\n.reg .pred p, q, r, s;\nW:\n"
                 "mbarrier.try_wait.parity.shared::cta.b64 p, [%0], 0;\n"
                 "mbarrier.try_wait.parity.shared::cta.b64 q, [%0+8], 0;\n"
                 "mbarrier.try_wait.parity.shared::cta.b64 r, [%0+16], 0;\n"
                 "mbarrier.try_wait.parity.shared::cta.b64 s, [%0+24], 0;\n"
                 "and.pred p, p, q;\nand.pred r, r, s;\nand.pred p, p, r;\n@!p bra W;\n}" ::"r"(bar) : "memory");
}
__device__ __forceinline__ void mbar_wait_cluster(uint32_t bar) {
    asm volatile("{\n.reg .pred p;\nW:\nmbarrier.try_wait.parity.acquire.cluster.shared::cta.b64 p, [%0], 0;\n@!p bra W;\n}" ::"r"(bar) : "memory");
}
__device__ __forceinline__ void tma4(uint32_t dst, const CUtensorMap* m, int c0, int c1, int c2, int c3, uint32_t bar, uint64_t pol) {
    asm volatile("cp.async.bulk.tensor.4d.shared::cluster.global.mbarrier::complete_tx::bytes.L2::cache_hint [%0], [%1, {%3,%4,%5,%6}], [%2], %7;"
                 ::"r"(dst), "l"(m), "r"(bar), "r"(c0), "r"(c1), "r"(c2), "r"(c3), "l"(pol) : "memory");
}
__device__ __forceinline__ void bar_sync(int id, int n) { asm volatile("bar.sync %0, %1;" ::"r"(id), "r"(n) : "memory"); }
__device__ __forceinline__ void bar_arrive(int id, int n) { asm volatile("bar.arrive %0, %1;" ::"r"(id), "r"(n) : "memory"); }
__device__ __forceinline__ void fence_async() { asm volatile("fence.proxy.async.shared::cta;" ::: "memory"); }

__device__ __forceinline__ uint32_t ldr1(const void* p) {
    uint32_t v; asm volatile("ld.relaxed.gpu.global.u32 %0, [%1];" : "=r"(v) : "l"(p) : "memory"); return v;
}
__device__ __forceinline__ uint2 ldr2(const void* p) {
    uint2 v; asm volatile("ld.relaxed.gpu.global.v2.u32 {%0,%1}, [%2];" : "=r"(v.x), "=r"(v.y) : "l"(p) : "memory"); return v;
}
__device__ __forceinline__ uint4 ldr4(const void* p) {
    uint4 v; asm volatile("ld.relaxed.gpu.global.v4.u32 {%0,%1,%2,%3}, [%4];"
                          : "=r"(v.x), "=r"(v.y), "=r"(v.z), "=r"(v.w) : "l"(p) : "memory"); return v;
}
__device__ __forceinline__ void str1(void* p, uint32_t v) { asm volatile("st.relaxed.gpu.global.u32 [%0], %1;" ::"l"(p), "r"(v) : "memory"); }
__device__ __forceinline__ void str2(void* p, uint32_t a, uint32_t b) {
    asm volatile("st.relaxed.gpu.global.v2.u32 [%0], {%1,%2};" ::"l"(p), "r"(a), "r"(b) : "memory");
}
__device__ __forceinline__ void str4(void* p, uint32_t a, uint32_t b, uint32_t c, uint32_t d) {
    asm volatile("st.relaxed.gpu.global.v4.u32 [%0], {%1,%2,%3,%4};" ::"l"(p), "r"(a), "r"(b), "r"(c), "r"(d) : "memory");
}
__device__ __forceinline__ void str64(void* p, uint32_t a, uint32_t b) {
    asm volatile("{\n.reg .b64 t;\nmov.b64 t, {%1,%2};\nst.relaxed.gpu.global.b64 [%0], t;\n}" ::"l"(p), "r"(a), "r"(b) : "memory");
}
__device__ __forceinline__ uint4 ldr64x2(const void* p) {
    uint4 v; asm volatile("{\n.reg .b64 s, t;\nld.relaxed.gpu.global.v2.b64 {s,t}, [%4];\nmov.b64 {%0,%1}, s;\nmov.b64 {%2,%3}, t;\n}"
                          : "=r"(v.x), "=r"(v.y), "=r"(v.z), "=r"(v.w) : "l"(p) : "memory"); return v;
}
__device__ __forceinline__ uint32_t tagf(float v, uint32_t tg) {
    uint32_t r; asm("lop3.b32 %0, %1, 0xFFFFFFFE, %2, 0xEA;" : "=r"(r) : "r"(__float_as_uint(v)), "r"(tg)); return r;
}
__device__ __forceinline__ float u2f(uint32_t v) { return __uint_as_float(v); }

__device__ __forceinline__ void sts1(uint32_t a, uint32_t v) { asm volatile("st.shared.u32 [%0], %1;" ::"r"(a), "r"(v) : "memory"); }
__device__ __forceinline__ void sts1f(uint32_t a, float v) { asm volatile("st.shared.f32 [%0], %1;" ::"r"(a), "f"(v) : "memory"); }
__device__ __forceinline__ void stsh(uint32_t a, uint32_t v) { asm volatile("st.shared.u16 [%0], %1;" ::"r"(a), "h"((unsigned short)v) : "memory"); }
__device__ __forceinline__ void sts2(uint32_t a, uint32_t x, uint32_t y) { asm volatile("st.shared.v2.u32 [%0], {%1,%2};" ::"r"(a), "r"(x), "r"(y) : "memory"); }
__device__ __forceinline__ void sts4(uint32_t a, uint32_t x, uint32_t y, uint32_t z, uint32_t w) {
    asm volatile("st.shared.v4.u32 [%0], {%1,%2,%3,%4};" ::"r"(a), "r"(x), "r"(y), "r"(z), "r"(w) : "memory");
}
__device__ __forceinline__ uint32_t lds1(uint32_t a) { uint32_t v; asm volatile("ld.shared.u32 %0, [%1];" : "=r"(v) : "r"(a) : "memory"); return v; }
__device__ __forceinline__ float lds1f(uint32_t a) { float v; asm volatile("ld.shared.f32 %0, [%1];" : "=f"(v) : "r"(a) : "memory"); return v; }
__device__ __forceinline__ float2 lds2f(uint32_t a) { float2 v; asm volatile("ld.shared.v2.f32 {%0,%1}, [%2];" : "=f"(v.x), "=f"(v.y) : "r"(a) : "memory"); return v; }
__device__ __forceinline__ uint4 lds4(uint32_t a) {
    uint4 v; asm volatile("ld.shared.v4.u32 {%0,%1,%2,%3}, [%4];" : "=r"(v.x), "=r"(v.y), "=r"(v.z), "=r"(v.w) : "r"(a) : "memory"); return v;
}
__device__ __forceinline__ float4 lds4f(uint32_t a) {
    float4 v; asm volatile("ld.shared.v4.f32 {%0,%1,%2,%3}, [%4];" : "=f"(v.x), "=f"(v.y), "=f"(v.z), "=f"(v.w) : "r"(a) : "memory"); return v;
}
__device__ __forceinline__ void ldsm4(uint32_t a, uint32_t (&r)[4]) {
    asm volatile("ldmatrix.sync.aligned.m8n8.x4.shared.b16 {%0,%1,%2,%3}, [%4];"
                 : "=r"(r[0]), "=r"(r[1]), "=r"(r[2]), "=r"(r[3]) : "r"(a) : "memory");
}
__device__ __forceinline__ void ldsm4t(uint32_t a, uint32_t (&r)[4]) {
    asm volatile("ldmatrix.sync.aligned.m8n8.x4.trans.shared.b16 {%0,%1,%2,%3}, [%4];"
                 : "=r"(r[0]), "=r"(r[1]), "=r"(r[2]), "=r"(r[3]) : "r"(a) : "memory");
}
__device__ __forceinline__ void stsm4t(uint32_t a, uint32_t r0, uint32_t r1, uint32_t r2, uint32_t r3) {
    asm volatile("stmatrix.sync.aligned.m8n8.x4.trans.shared.b16 [%0], {%1,%2,%3,%4};"
                 ::"r"(a), "r"(r0), "r"(r1), "r"(r2), "r"(r3) : "memory");
}
__device__ __forceinline__ void mma16816(float (&d)[4], const uint32_t (&a)[4], uint32_t b0, uint32_t b1) {
    asm volatile("mma.sync.aligned.m16n8k16.row.col.f32.bf16.bf16.f32 {%0,%1,%2,%3}, {%4,%5,%6,%7}, {%8,%9}, {%0,%1,%2,%3};"
                 : "+f"(d[0]), "+f"(d[1]), "+f"(d[2]), "+f"(d[3])
                 : "r"(a[0]), "r"(a[1]), "r"(a[2]), "r"(a[3]), "r"(b0), "r"(b1));
}
__device__ __forceinline__ uint32_t packbf(float lo, float hi) {
    uint32_t r; asm("cvt.rn.bf16x2.f32 %0, %1, %2;" : "=r"(r) : "f"(hi), "f"(lo)); return r;
}
__device__ __forceinline__ float bflo(uint32_t w) { return __uint_as_float(w << 16); }
__device__ __forceinline__ float bfhi(uint32_t w) { return __uint_as_float(w & 0xffff0000u); }
__device__ __forceinline__ void split2(float a, float b, uint32_t& hi, uint32_t& lo) {
    hi = packbf(a, b);
    lo = packbf(a - bflo(hi), b - bfhi(hi));
}
__device__ __forceinline__ uint32_t ordf(uint32_t u) { return u ^ ((uint32_t)((int)u >> 31) & 0x7FFFFFFFu); }
__device__ __forceinline__ void red_max(uint32_t a, uint32_t v) { asm volatile("red.shared.max.s32 [%0], %1;" ::"r"(a), "r"(v) : "memory"); }
__device__ __forceinline__ float fsel(bool c, float a, float b) {
    float r; asm("{\n.reg .pred p;\nsetp.ne.b32 p, %3, 0;\nselp.f32 %0, %1, %2, p;\n}" : "=f"(r) : "f"(a), "f"(b), "r"((int)c)); return r;
}
__device__ __forceinline__ float ex2(float x) { float y; asm("ex2.approx.ftz.f32 %0, %1;" : "=f"(y) : "f"(x)); return y; }

__device__ __forceinline__ int vpos(int k32) {
    return (((k32 & 7) >> 1) * 8 + (k32 >> 4) * 4 + ((k32 >> 3) & 1) * 2 + (k32 & 1)) * 2;
}

__device__ __forceinline__ void wg_fence()  { asm volatile("wgmma.fence.sync.aligned;" ::: "memory"); }
__device__ __forceinline__ void wg_commit() { asm volatile("wgmma.commit_group.sync.aligned;" ::: "memory"); }
template <int N> __device__ __forceinline__ void wg_wait() { asm volatile("wgmma.wait_group.sync.aligned %0;" ::"n"(N) : "memory"); }
__device__ __forceinline__ uint64_t mkdesc(uint32_t addr) {
    return (uint64_t)((addr & 0x3FFFF) >> 4) | ((uint64_t)64 << 16) | ((uint64_t)64 << 32) | ((uint64_t)1 << 62);
}
template <int TA>
__device__ __forceinline__ void wgmma_n32(float (&d)[16], uint64_t da, uint64_t db, int acc) {
    asm volatile("{\n.reg .pred p;\nsetp.ne.b32 p, %18, 0;\n"
                 "wgmma.mma_async.sync.aligned.m64n32k16.f32.bf16.bf16 "
                 "{%0,%1,%2,%3,%4,%5,%6,%7,%8,%9,%10,%11,%12,%13,%14,%15}, %16, %17, p, 1, 1, %19, 0;\n}"
                 : "+f"(d[0]), "+f"(d[1]), "+f"(d[2]), "+f"(d[3]), "+f"(d[4]), "+f"(d[5]), "+f"(d[6]), "+f"(d[7]),
                   "+f"(d[8]), "+f"(d[9]), "+f"(d[10]), "+f"(d[11]), "+f"(d[12]), "+f"(d[13]), "+f"(d[14]), "+f"(d[15])
                 : "l"(da), "l"(db), "r"(acc), "n"(TA));
}
__device__ __forceinline__ void reg_fence16(float (&d)[16]) {
#pragma unroll
    for (int i = 0; i < 16; i++) asm volatile("" : "+f"(d[i])::"memory");
}

template <bool TRANS>
__device__ __forceinline__ void gemv128(uint32_t tile, uint32_t vec, uint32_t bars, int warp, int lane, float& r0, float& r1) {
    const int m = lane >> 3, r8 = lane & 7;
    uint32_t bq[4][4];
#pragma unroll
    for (int i = 0; i < 4; i++) {
        uint4 t = lds4(vec + i * 128 + ((lane >> 2) & 1) * 64 + (lane & 3) * 16);
        bq[i][0] = t.x; bq[i][1] = t.y; bq[i][2] = t.z; bq[i][3] = t.w;
    }
    float d0[4] = {0.f, 0.f, 0.f, 0.f}, d1[4] = {0.f, 0.f, 0.f, 0.f};
    if (TRANS) {
        const uint32_t a0 = tile + (warp >> 2) * 4096 + ((m >> 1) * 8 + r8) * 128 + ((((warp & 3) * 2 + (m & 1)) ^ r8) << 4);
#pragma unroll
        for (int i = 0; i < 4; i++) {
            mbar_wait(bars + i * 8);
            uint32_t a[4], c[4];
            ldsm4t(a0 + i * 8192, a);
            ldsm4t(a0 + i * 8192 + 2048, c);
            mma16816(d0, a, bq[i][0], bq[i][1]);
            mma16816(d1, c, bq[i][2], bq[i][3]);
        }
    } else {
        mbar_wait(bars + (warp >> 1) * 8);
        const uint32_t a0 = tile + (warp >> 1) * 8192 + ((warp & 1) * 16 + (m & 1) * 8 + r8) * 128;
#pragma unroll
        for (int i = 0; i < 4; i++) {
            uint32_t a[4], c[4];
            ldsm4(a0 + (i >> 1) * 4096 + ((((i & 1) * 4 + (m >> 1)) ^ r8) << 4), a);
            ldsm4(a0 + (i >> 1) * 4096 + ((((i & 1) * 4 + 2 + (m >> 1)) ^ r8) << 4), c);
            mma16816(d0, a, bq[i][0], bq[i][1]);
            mma16816(d1, c, bq[i][2], bq[i][3]);
        }
    }
    r0 = (d0[0] + d0[1]) + (d1[0] + d1[1]);
    r1 = (d0[2] + d0[3]) + (d1[2] + d1[3]);
}

__device__ __forceinline__ void step32(uint32_t rows, uint32_t vecaddr, int lane, float (&d0)[4], float (&d1)[4]) {
    const int m = lane >> 3, r8 = lane & 7;
    const uint32_t a0 = rows + ((m >> 1) * 8 + r8) * 32 + (((m & 1) ^ (r8 >> 2)) << 4);
    uint4 t = lds4(vecaddr);
    uint32_t a[4], c[4];
    ldsm4t(a0, a);
    ldsm4t(a0 + 512, c);
    mma16816(d0, a, t.x, t.y);
    mma16816(d1, c, t.z, t.w);
}

__device__ __forceinline__ void reduce16_publish(uint32_t sb, float (&d0)[4], float (&d1)[4], int tid, int warp, int lane, unsigned char* dst, uint32_t tg) {
    if ((lane & 3) == 0) {
        sts1f(sb + S_R16 + (lane >> 2) * 32 + warp * 4, (d0[0] + d0[1]) + (d1[0] + d1[1]));
        sts1f(sb + S_R16 + ((lane >> 2) + 8) * 32 + warp * 4, (d0[2] + d0[3]) + (d1[2] + d1[3]));
    }
    bar_sync(2, 256);
    if (tid < 32) {
        float4 u = lds4f(sb + S_R16 + (tid & 15) * 32), v = lds4f(sb + S_R16 + (tid & 15) * 32 + 16);
        str1(dst + (tid & 15) * 4 + (tid >> 4) * 4096, tagf(((u.x + u.y) + (u.z + u.w)) + ((v.x + v.y) + (v.z + v.w)), tg));
    }
}

__device__ __forceinline__ uint32_t xo2(uint32_t a, uint32_t b, uint32_t t) {
    uint32_t r; asm("lop3.b32 %0, %1, %2, %3, 0x7E;" : "=r"(r) : "r"(a), "r"(b), "r"(t)); return r;
}
__device__ __forceinline__ uint32_t or3(uint32_t a, uint32_t b, uint32_t c) {
    uint32_t r; asm("lop3.b32 %0, %1, %2, %3, 0xFE;" : "=r"(r) : "r"(a), "r"(b), "r"(c)); return r;
}
__device__ __forceinline__ uint32_t bad2(const uint2& v, uint32_t tg) { return xo2(v.x, v.y, tg); }
__device__ __forceinline__ uint32_t bad4(const uint4& v, uint32_t tg) { return or3(xo2(v.x, v.y, tg), xo2(v.z, v.w, tg), 0); }
__device__ __forceinline__ bool nz4(const uint4& v) { return v.x != 0 && v.y != 0 && v.z != 0 && v.w != 0; }
__device__ __forceinline__ uint32_t clk32() { uint32_t c; asm volatile("mov.u32 %0, %%clock;" : "=r"(c)); return c; }
__device__ __forceinline__ void wait_until(uint32_t t0, uint32_t dt) {
#pragma unroll 1
    while ((int)(clk32() - t0 - dt) < 0) {}
}
__device__ __forceinline__ uint32_t mbar_mask4(uint32_t bar) {
    uint32_t m;
    asm volatile("{\n.reg .pred p, q, r, s;\n.reg .b32 a, b;\n"
                 "mbarrier.test_wait.parity.shared::cta.b64 p, [%1], 0;\n"
                 "mbarrier.test_wait.parity.shared::cta.b64 q, [%1+8], 0;\n"
                 "mbarrier.test_wait.parity.shared::cta.b64 r, [%1+16], 0;\n"
                 "mbarrier.test_wait.parity.shared::cta.b64 s, [%1+24], 0;\n"
                 "selp.u32 a, 1, 0, p;\nselp.u32 b, 2, 0, q;\nor.b32 a, a, b;\nselp.u32 b, 4, 0, r;\nor.b32 a, a, b;\n"
                 "selp.u32 b, 8, 0, s;\nor.b32 a, a, b;\nredux.sync.and.b32 %0, a, 0xffffffff;\n}" : "=r"(m) : "r"(bar) : "memory");
    return m;
}
__device__ __forceinline__ uint32_t probe_near(unsigned char* sp, uint32_t po, uint32_t sink) {
    uint32_t best0 = ~0u, best1 = ~0u;
#pragma unroll 1
    for (int r = 0; r < 5; r++) {
        uint32_t v; const uint32_t t0 = clk32();
        asm volatile("atom.relaxed.gpu.global.exch.b32 %0, [%1], %2;" : "=r"(v) : "l"(sp + po + (r & 1) * 4096), "r"(r) : "memory");
        sts1(sink, v);
        const uint32_t dt = clk32() - t0;
        if (r & 1) best1 = min(best1, dt); else best0 = min(best0, dt);
    }
    return (uint32_t)(best1 < best0) ^ (__popc(po & 0xB2000u) & 1u);
}
#define PIN(x) asm volatile("" : "+l"(x))
#define SPIN_CHECK(it) if (++(it) > SPIN_MAX) __trap()

__device__ __forceinline__ void mod2_tile(uint32_t sb, unsigned char* sp, uint32_t bars, int b, int nt, int lane, uint32_t tg) {
    const int m = lane >> 3, r8 = lane & 7, q = lane & 3;
    const uint32_t a0 = sb + S_MOD2 + ((m >> 1) * 8 + r8) * 64 + (((nt * 2 + (m & 1)) ^ (r8 >> 1)) << 4);
    const uint32_t v0 = sb + S_SC + (b >> 6) * 1024 + ((lane >> 2) & 1) * 64 + q * 16;
    float d0[4] = {0.f, 0.f, 0.f, 0.f}, d1[4] = {0.f, 0.f, 0.f, 0.f};
#pragma unroll 1
    for (int c = 0; c < 2; c++) {
        mbar_wait(bars + (C_MOD2 + c) * 8);
#pragma unroll
        for (int i = 0; i < 4; i++) {
            const uint4 t = lds4(v0 + (c * 4 + i) * 128);
            uint32_t a[4], e[4];
            ldsm4t(a0 + c * 8192 + i * 2048, a); ldsm4t(a0 + c * 8192 + i * 2048 + 1024, e);
            mma16816(d0, a, t.x, t.y); mma16816(d1, e, t.z, t.w);
        }
    }
    const float r0 = (d0[0] + d0[1]) + (d1[0] + d1[1]), r1 = (d0[2] + d0[3]) + (d1[2] + d1[3]);
    const float t0 = __shfl_sync(~0u, r0, lane & 28), t1 = __shfl_sync(~0u, r1, lane & 28);
    str1(sp + G_MOD2 + spread(b * 128 + nt * 64 + (q & 1) * 32 + (lane >> 2) * 4) + (q >> 1) * 4096, tagf((q & 1) ? t1 : t0, tg));
}

__global__ void __cluster_dims__(2, 1, 1) __launch_bounds__(NTHR, 1) fused_decode_kernel(const __grid_constant__ Params p) {
    extern __shared__ __align__(1024) unsigned char smem_raw[];
    const uint32_t sb = (uint32_t)__cvta_generic_to_shared(smem_raw);
    const int tid = threadIdx.x, lane = tid & 31;
    const int warp = __shfl_sync(~0u, tid >> 5, 0);
    const int b = blockIdx.x, h = b >> 2, j = b & 3, rank = b & 1, pair = b >> 1;
    const uint32_t bars = sb + S_BAR;
    unsigned char* const sp = p.s;
    const uint32_t t_start = clk32();

    if (warp == 11) {
        float d[4] = {0.f, 0.f, 0.f, 0.f};
        const uint32_t zz = t_start & 0x00010001u, z[4] = {zz, zz, zz, zz};
        mma16816(d, z, zz, zz);
        bar_sync(1, NTHR - 32);
        uint32_t done = 0;
#pragma unroll 1
        for (int i = 0; i < 4096 && done < 2; i++) {
            mma16816(d, z, zz, zz);
            __nanosleep(200);
            done += mbar_mask4(bars + B_F * 8) & 1;
        }
        if (d[0] == 1.f) sts1f(sb + S_EP + 12, d[1]);
        return;
    }
    if (warp == 8) {
        TS(30);
        if (lane == 0) {
            mbar_init(bars, 1);
            asm volatile("fence.mbarrier_init.release.cluster;" ::: "memory");
            mbar_expect_tx(bars, 8192);
            tma4(sb + S_MOD1, &p.m[0], (b >> 1) * 16, (b & 1) * 256, 0, 0, bars, POL_FIRST);
            TS(28);
#pragma unroll
            for (int i = 1; i < NBAR; i++) mbar_init(bars + i * 8, i == B_UK ? 8 : i == B_O ? 4 : 1);
            asm volatile("fence.mbarrier_init.release.cluster;" ::: "memory");
            mbar_expect_tx(bars + B_X * 8, 8192); mbar_expect_tx(bars + (B_X + 1) * 8, 8192);
        }
        __syncwarp();
        TS(27);
        bar_arrive(1, NTHR - 32);
        {
            const int c = lane + 1;
            int mi = 1, k = c - C_WQ, c0 = 0, c1 = j * 128, d1 = 32, c2 = h * 2, c3 = 0, dst = S_WQ;
            if (c >= C_WUK)  { mi = 2; k = c - C_WUK; dst = S_WUK; }
            if (c >= C_CKV)  { mi = 3; k = c - C_CKV; dst = S_CKV; c1 = pair * 128 + (k >> 2) * 64; d1 = 0; c2 = rank * 4 + (k & 3); }
            if (c >= C_T1)   { const int x = (c - C_T1) & 1; k = (c - C_T1) >> 1; dst = x ? S_XCH : S_CKV + 6 * 8192; c1 = pair * 128 + 64; c2 = (rank ^ x) * 4 + 2 + k; }
            if (c >= C_WUV)  { mi = 4; k = c - C_WUV; dst = S_WUV; c1 = j * 16; c2 = k * 2; c3 = h * 2; }
            if (c >= C_WUV + 4) { mi = 5; k = c - C_WO; dst = S_WO; c0 = (b & 15) * 32; c1 = (b >> 4) * 512; d1 = 128; c2 = 0; c3 = 0; }
            if (c == C_MOD2 || c == C_MOD2 + 1) { mi = 8; k = c - C_MOD2; dst = S_MOD2; c0 = 1024 + (b & 63) * 32; c1 = (b >> 6) * 256; }
            if (c >= C_W1)   { mi = 6; k = c - C_W1; dst = S_W1; c0 = b * 16; c1 = 0; d1 = 256; }
            if (c >= C_W2)   { mi = 7; k = c - C_W2; dst = S_W2; c0 = 0; c1 = b * 32; d1 = 16; }
            const uint32_t wa = (uint32_t)c0 | (uint32_t)(c1 + k * d1) << 16;
            const bool keep = c >= C_T1 && c < C_WUV;
            const uint32_t wb = (uint32_t)c2 | (uint32_t)c3 << 8 | (uint32_t)mi << 14 | (uint32_t)keep << 18 | (uint32_t)((dst >> 13) + k) << 24;
            const int nch = b < NFFN ? NCHUNK : C_W1;
#pragma unroll 1
            for (int i = 1; i < nch; i++) {
                const uint32_t ua = __shfl_sync(~0u, wa, i - 1), ub = __shfl_sync(~0u, wb, i - 1);
                if (i == C_T1 + 1) mbar_wait(bars + B_UK * 8);
                if (i == C_W1) mbar_wait(bars + B_QK * 8);
                if (i >= WIN) mbar_wait(bars + (i - WIN) * 8);
                wait_until(t_start, p.sched[i]);
                if (lane == 0) {
                    mbar_expect_tx(bars + i * 8, 8192);
                    tma4(sb + (ub >> 24) * 8192, &p.m[(ub >> 14) & 15], ua & 0xffff, ua >> 16, ub & 0xff, (ub >> 8) & 0x3f, bars + i * 8,
                         (ub >> 18 & 1) ? POL_NORMAL : POL_FIRST);
                }
            }
        }
        TS(20);
        return;
    }
    if (warp == 9) {
        const int col = (lane & 1) * 4 + (lane & 2) + ((lane >> 2) & 1);
        const float be = __bfloat162float(p.b2[(b & 63) * 8 + col]);
        const uint32_t pr0 = G_PROBE + b * 32, pr4 = G_H4 + pair * 131072 + 65536 + rank * 256;
        if (lane < 4) str4(sp + pr0 + (lane & 2) * 2048 + (lane & 1) * 16, 0, 0, 0, 0);
        __syncwarp();
        uint32_t beta = 0;
        if (lane == 0) { beta = probe_near(sp, pr0, sb + S_EP + 12); sts1(sb + S_EP + 4, beta); }
        __syncwarp();
        bar_sync(8, 64);
        if (lane == 0) mbar_arrive(bars + B_BETA * 8);
        TS(69);
        const uint32_t ep = lds1(sb + S_EP);
        const uint32_t tg = ~ep & 1u;
        beta = __shfl_sync(~0u, beta, 0);
        {
            const uint32_t prev = ldr1(sp + pr4 + 128);
            if (lane < 4) str4(sp + pr4 + (lane & 2) * 2048 + (lane & 1) * 16, 0, 0, 0, 0);
            __syncwarp();
            uint32_t w = 0;
            if (lane == 0) {
                const uint32_t beta4 = probe_near(sp, pr4, sb + S_EP + 12);
                const uint32_t held = (prev & 24) ^ (8u << beta4);
                w = tg | beta4 << 1 | (held >> (3 + beta4) & 1) << 2 | held;
                sts1(sb + S_EP + 8, w);
                mbar_arrive(bars + B_BETA4 * 8);
            }
            w = __shfl_sync(~0u, w, 0);
            if (lane < 2) str4(sp + pr4 + 128 + lane * 16, w, w, w, w);
        }
        TS(70);
        const unsigned char* sg = sp + pick(G_MOD2 + spread((lane & 8) * 1024 + 6144 + (b & 63) * 32 + col * 4), beta);
        const unsigned char* s7 = sp + pick(G_H7 + (b & 63) * 8192 + lane * 16, beta);
        const unsigned char* s7c = s7 + (lane < 2 * (NFFN - 80) ? 2560 : 0);
        mod2_tile(sb, sp, bars, b, 0, lane, tg);
        TS(29);
        if (b >= 64) return;
        mbar_wait(bars + B_F * 8);
        uint32_t w; int it = 0;
#pragma unroll 1
        do { w = ldr1(sg); SPIN_CHECK(it); } while (__any_sync(~0u, (w ^ tg) & 1));
        const float gb = u2f(w) + __shfl_xor_sync(~0u, u2f(w), 8);
        bar_sync(10, 320);
        const uint32_t t_6 = clk32();
        const float x2 = fmaf(gb, be, lds1f(sb + S_X2 + col * 4));
        TS(21);
        wait_until(t_6, p.tm[D_H7]);
        uint4 y[6];
#pragma unroll 1
        do {
#pragma unroll
            for (int i = 0; i < 5; i++) y[i] = ldr4(s7 + i * 512);
            y[5] = ldr4(s7c);
            SPIN_CHECK(it);
        } while (__any_sync(~0u, or3(or3(bad4(y[0], tg), bad4(y[1], tg), bad4(y[2], tg)), or3(bad4(y[3], tg), bad4(y[4], tg), bad4(y[5], tg)), 0) & 1));
        if (lane >= 2 * (NFFN - 80)) y[5] = make_uint4(0, 0, 0, 0);
        const float s0 = ((u2f(y[0].x) + u2f(y[1].x)) + (u2f(y[2].x) + u2f(y[3].x))) + (u2f(y[4].x) + u2f(y[5].x));
        const float s1 = ((u2f(y[0].y) + u2f(y[1].y)) + (u2f(y[2].y) + u2f(y[3].y))) + (u2f(y[4].y) + u2f(y[5].y));
        const float s2 = ((u2f(y[0].z) + u2f(y[1].z)) + (u2f(y[2].z) + u2f(y[3].z))) + (u2f(y[4].z) + u2f(y[5].z));
        const float s3 = ((u2f(y[0].w) + u2f(y[1].w)) + (u2f(y[2].w) + u2f(y[3].w))) + (u2f(y[4].w) + u2f(y[5].w));
        {
            const bool b1 = lane & 2, b2 = lane & 4;
            const float k0 = (b1 ? s2 : s0) + __shfl_xor_sync(~0u, b1 ? s0 : s2, 2), k1 = (b1 ? s3 : s1) + __shfl_xor_sync(~0u, b1 ? s1 : s3, 2);
            float k = (b2 ? k1 : k0) + __shfl_xor_sync(~0u, b2 ? k0 : k1, 4);
            k += __shfl_xor_sync(~0u, k, 8); k += __shfl_xor_sync(~0u, k, 16);
            if (lane < 8) p.out[b * 8 + col] = __float2bfloat16(fmaf(gb, k, x2));
            if (b == 0 && lane == 8) str1(sp + G_EPOCH, ep + 1);
        }
        TS(22);
        return;
    }

    if (warp == 10) {
        const float b1v = __bfloat162float(p.b1[(b < NFFN ? b * 16 : 0) + (lane & 15)]);
        bar_sync(1, NTHR - 32);
        const uint32_t tg = ~lds1(sb + S_EP) & 1u;
        mbar_wait(bars + B_BETA * 8);
        const uint32_t beta = lds1(sb + S_EP + 4);
        const unsigned char* sm_a = sp + pick(G_ML + spread(lane * 256 + h * 4), beta);
        const unsigned char* sm_b = sp + pick(G_ML + spread((lane + 32) * 256 + h * 4), beta);
        mbar_wait(bars + B_QK * 8);
        wait_until(clk32(), p.tm[D_H4]);
        wait_until(t_start, p.tm[T_H4] - p.tm[A_H4] / 2);
        uint32_t ma, mb, la, lb; int it = 0;
        TS(76);
#pragma unroll 1
        do {
            ma = ldr1(sm_a); mb = ldr1(sm_b); la = ldr1(sm_a + 128); lb = ldr1(sm_b + 128);
            SPIN_CHECK(it);
        } while (__any_sync(~0u, (xo2(ma, mb, tg) | xo2(la, lb, tg)) & 1));
        TS(77);
        float M = fmaxf(u2f(ma), u2f(mb));
#pragma unroll
        for (int o = 16; o; o >>= 1) M = fmaxf(M, __shfl_xor_sync(~0u, M, o));
        const float wa = ex2(u2f(ma) - M), wb = ex2(u2f(mb) - M);
        float L = wa * u2f(la) + wb * u2f(lb);
#pragma unroll
        for (int o = 16; o; o >>= 1) L += __shfl_xor_sync(~0u, L, o);
        L = __fdividef(1.f, L);
        sts1f(sb + S_ML + lane * 4, wa * L); sts1f(sb + S_ML + 128 + lane * 4, wb * L);
        __syncwarp();
        if (lane == 0) mbar_arrive(bars + B_W * 8);
        TS(78);
        mod2_tile(sb, sp, bars, b, 1, lane, tg);
        if (b < NFFN) {
            const uint32_t a = sb + S_RED + (lane & 15) * 32 + (lane >> 4) * 16;
            const uint32_t as = sb + S_RED + 1536 + (lane >> 4) * 16;
            bar_sync(9, 288);
            const float4 sa = lds4f(as + 8 * 32), ta = lds4f(as + 6 * 32), tc = lds4f(as + 7 * 32);
            const float4 U = lds4f(a), G = lds4f(a + 512), S = lds4f(a + 1024);
            float mu = (sa.x + sa.y) + (sa.z + sa.w), ex = ((ta.x + ta.y) + (ta.z + ta.w)) + ((tc.x + tc.y) + (tc.z + tc.w));
            float us = (U.x + U.y) + (U.z + U.w), gs = (G.x + G.y) + (G.z + G.w), ss = (S.x + S.y) + (S.z + S.w);
            mu += __shfl_xor_sync(~0u, mu, 16); ex += __shfl_xor_sync(~0u, ex, 16);
            us += __shfl_xor_sync(~0u, us, 16); gs += __shfl_xor_sync(~0u, gs, 16); ss += __shfl_xor_sync(~0u, ss, 16);
            mu *= 1.f / 512.f;
            float rstd;
            asm("rsqrt.approx.ftz.f32 %0, %1;" : "=f"(rstd) : "f"(fmaxf(fmaf(ex, 1.f / 512.f, -mu * mu), 0.f) + 1e-5f));
            const float pre = (us - mu * gs) * rstd + (ss + b1v);
            const float z = pre * fmaf(pre * pre, 0.044715f * 2.302208198f, 2.302208198f);
            sts1f(sb + S_STAT + (lane & 15) * 4, __fdividef(pre, 1.f + ex2(fminf(-z, 126.f))));
            bar_arrive(10, b < 64 ? 320 : 288);
        }
        return;
    }

    const int g = lane >> 2, q = lane & 3;
    const int wg = warp >> 2, wq = warp & 3;
    const uint32_t ep0 = ldr1(sp + G_EPOCH);
    const uint32_t tg = ~ep0 & 1u;
    const uint32_t cw = *reinterpret_cast<const uint32_t*>(p.c + tid * 2);
    const uint4 xa = *reinterpret_cast<const uint4*>(p.x + lane * 16), xb = *reinterpret_cast<const uint4*>(p.x + lane * 16 + 8);
    const uint32_t xw2 = *reinterpret_cast<const uint32_t*>(p.x + tid * 2);
    const float xm = __bfloat162float(p.x[j * 128 + (tid & 127)]);
    {
        uint32_t z = ~0u, zv = tg ^ 1u;
        if (tid < 4) z = G_H1 + spread((b & 1) * 4096 + (b >> 1) * 64 + tid * 16);
        else if (tid >= 8 && tid < 16) z = G_MOD2 + spread(b * 128 + (tid & 7) * 16);
        else if (tid >= 112 && tid < 120) z = G_H6 + spread(b * 128 + (tid & 7) * 16);
        else if (tid >= 16 && tid < 32) { const uint32_t o = G_ML + spread(pair * 256 + (tid & 15) * 16) + rank * 4096; str4(sp + o, zv, zv, zv, zv); }
        else if (tid >= 32 && tid < 64) z = G_H2 + spread(b * 512 + lane * 16);
        else if (tid >= 64 && tid < 96) z = G_H5 + spread(b * 512 + lane * 16);
        else if (tid >= 96 && tid < 112) { z = G_H3 + spread((j * 2 + ((tid >> 3) & 1)) * 4096 + h * 128 + (tid & 7) * 16); zv = 0; }
        if (z != ~0u) { str4(sp + z, zv, zv, zv, zv); str4(sp + z + 4096, zv, zv, zv, zv); }
    }
    if (tid == 0) sts1(sb + S_EP, ep0);
    if (tid < 64) sts1(sb + S_MAX + tid * 4, 0x80000000u);
    sts1(sb + S_ONES + tid * 4, 0x3F803F80u);
    {
        const float c0 = bflo(cw), c1 = bfhi(cw);
        const float s0 = __fdividef(c0, 1.f + __expf(fminf(-c0, 80.f))), s1 = __fdividef(c1, 1.f + __expf(fminf(-c1, 80.f)));
        uint32_t hi, lo; split2(s0, s1, hi, lo);
        const uint32_t a = sb + S_SC + (tid >> 4) * 128 + vpos((tid & 15) * 2);
        sts1(a, hi); sts1(a + 64, lo);
    }
    TS0(0);
    bar_sync(1, NTHR - 32);
    if (warp == 7) bar_arrive(8, 64);

    const uint32_t vlane = (g & 1) * 64 + q * 16;

    {
        float d0[4] = {0.f, 0.f, 0.f, 0.f}, d1[4] = {0.f, 0.f, 0.f, 0.f};
        mbar_wait(bars + C_MOD1 * 8);
        step32(sb + S_MOD1 + warp * 1024, sb + S_SC + ((b & 1) * 8 + warp) * 128 + vlane, lane, d0, d1);
        reduce16_publish(sb, d0, d1, tid, warp, lane, sp + G_H1 + spread((b & 1) * 4096 + (b >> 1) * 64), tg);
    }
    TS0(1);
    float mean1, rstd1;
    {
        const uint32_t w[8] = {xa.x, xa.y, xa.z, xa.w, xb.x, xb.y, xb.z, xb.w};
        float s = 0.f;
#pragma unroll
        for (int i = 0; i < 8; i++) s += bflo(w[i]) + bfhi(w[i]);
#pragma unroll
        for (int o = 16; o; o >>= 1) s += __shfl_xor_sync(~0u, s, o);
        mean1 = s * (1.f / 512.f);
        float v = 0.f;
#pragma unroll
        for (int i = 0; i < 8; i++) { float a = bflo(w[i]) - mean1, c = bfhi(w[i]) - mean1; v += a * a + c * c; }
#pragma unroll
        for (int o = 16; o; o >>= 1) v += __shfl_xor_sync(~0u, v, o);
        rstd1 = rsqrtf(v * (1.f / 512.f) + 1e-5f);
    }
    if (tid < 128) {
        const unsigned char* s0 = sp + G_H1 + j * 512 + tid * 4;
        const unsigned char* s1 = s0 + 8192;
        uint4 a; int it = 0;
        wait_until(t_start, p.tm[T_H1]);
#pragma unroll 1
        do {
            a.x = ldr1(s0); a.y = ldr1(s1); a.z = ldr1(s0 + 2048); a.w = ldr1(s1 + 2048);
            SPIN_CHECK(it);
        } while (bad4(a, tg) & 1);
        const float hv = (xm - mean1) * rstd1 * (1.f + (u2f(a.z) + u2f(a.w))) + (u2f(a.x) + u2f(a.y));
        uint32_t hi, lo; split2(hv, 0.f, hi, lo);
        const uint32_t ad = sb + S_VEC + (tid >> 5) * 128 + vpos(tid & 31);
        stsh(ad, hi); stsh(ad + 64, lo);
    }
    TS0(2);
    bar_sync(2, 256);
    {
        float r0, r1;
        gemv128<true>(sb + S_WQ, sb + S_VEC, bars + C_WQ * 8, warp, lane, r0, r1);
        const float t0 = __shfl_sync(~0u, r0, lane & 28), t1 = __shfl_sync(~0u, r1, lane & 28);
        str1(sp + G_H2 + spread(b * 512 + warp * 64 + (q & 1) * 32 + g * 4) + (q >> 1) * 4096, tagf((q & 1) ? t1 : t0, tg));
    }
    TS0(3);
    mbar_wait(bars + B_BETA * 8);
    const uint32_t beta = lds1(sb + S_EP + 4);
    bar_sync(2, 256);
    if (tid < 128) {
        const unsigned char* src = sp + pick(G_H2 + spread(h * 2048 + tid * 4), beta);
        uint4 a; int it = 0;
#pragma unroll 1
        do {
            a.x = ldr1(src); a.y = ldr1(src + 512); a.z = ldr1(src + 1024); a.w = ldr1(src + 1536);
            SPIN_CHECK(it);
        } while (bad4(a, tg) & 1);
        const float qv = ((u2f(a.x) + u2f(a.y)) + (u2f(a.z) + u2f(a.w))) * (0.08838834764831845f * 1.4426950408889634f);
        uint32_t hi, lo; split2(qv, 0.f, hi, lo);
        const uint32_t ad = sb + S_VEC + (tid >> 5) * 128 + vpos(tid & 31);
        stsh(ad, hi); stsh(ad + 64, lo);
    }
    TS0(4);
    bar_sync(2, 256);
    {
        float r0, r1;
        gemv128<false>(sb + S_WUK, sb + S_VEC, bars + C_WUK * 8, warp, lane, r0, r1);
        const float n0 = __shfl_down_sync(~0u, r0, 4), m0 = __shfl_up_sync(~0u, r1, 4);
        const uint32_t w = (g & 1) ? packbf(m0, r1) : packbf(r0, n0);
        const uint32_t w2 = __shfl_sync(~0u, w, lane & 28);
        if (q < 2) {
            const int chunk = ((warp & 3) * 2 + (g & 1)) ^ (h & 7);
            str1(sp + G_H3 + (j * 2 + (warp >> 2)) * 8192 + q * 4096 + h * 128 + chunk * 16 + (g >> 1) * 4, w2 ^ 0xFFFF0000u);
        }
        if (lane == 0) mbar_arrive(bars + B_UK * 8);
    }
    TS0(5);
    {
        const unsigned char* src[6];
#pragma unroll
        for (int i = 0; i < 6; i++) src[i] = sp + pick(G_H3 + (i < 4 ? rank * 4 + i : (rank ^ 1) * 4 + i - 2) * 8192 + tid * 16, beta);
        uint4 v[6];
        wait_until(t_start, p.tm[T_H3]);
#pragma unroll
        for (int i = 0; i < 6; i++) v[i] = ldr4(src[i]);
        int it = 0;
#pragma unroll 1
        while (true) {
            bool ok = true;
#pragma unroll
            for (int i = 0; i < 6; i++) if (!nz4(v[i])) { v[i] = ldr4(src[i]); ok = false; }
            if (__all_sync(~0u, ok)) break;
            SPIN_CHECK(it);
        }
        TS0(31);
#pragma unroll
        for (int i = 0; i < 6; i++)
            sts4(sb + S_QABS + i * 4096 + tid * 16, v[i].x ^ 0xFFFF0000u, v[i].y ^ 0xFFFF0000u, v[i].z ^ 0xFFFF0000u, v[i].w ^ 0xFFFF0000u);
        fence_async();
        bar_sync(2, 256);
    }
    TS0(6);
    if (wg) {
        uint32_t bw; int it = 0;
#pragma unroll 1
        do { bw = ldr1(sp + G_H4 + 65536 + 128 + ((tid & 127) >> 1) * 131072 + (tid & 1) * 256); SPIN_CHECK(it); } while (__any_sync(~0u, (bw ^ tg) & 1));
        const uint32_t mb = __ballot_sync(~0u, bw & 2), mt = __ballot_sync(~0u, bw & 4);
        if (lane == 0) sts2(sb + S_B4 + wq * 8, mb, mt);
    }
    if (b < NFFN) {
        unsigned char* d7 = sp + G_H7 + (tid >> 2) * 8192 + b * 32 + (tid & 3) * 8;
        str2(d7, tg ^ 1, tg ^ 1); str2(d7 + 4096, tg ^ 1, tg ^ 1);
    }
    mbar_wait(bars + B_BETA4 * 8);
    const uint32_t rec = lds1(sb + S_EP + 8), tg4w = rec >> 2 & 1;
    unsigned char* const h4dst = sp + pick(G_H4 + pair * 131072 + spread(q * 2048 + wq * 256 + rank * 128 + g * 8), rec >> 1);
    {
        float s[16];
#pragma unroll
        for (int i = 0; i < 16; i++) s[i] = 0.f;
        const uint32_t xo = (wg ? S_XBUF1 : S_XBUF0) + (tid & 127) * 16;
#pragma unroll 1
        for (int cg = 0; cg < 4 - 2 * wg; cg++) {
            mbar_wait(bars + (C_CKV + wg * 4 + cg) * 8);
            const uint64_t da = mkdesc(sb + S_CKV + (wg * 4 + cg) * 8192), db = mkdesc(sb + S_QABS + cg * 4096);
            wg_fence();
#pragma unroll
            for (int k = 0; k < 4; k++) wgmma_n32<0>(s, da + k * 2, db + k * 2, 1);
            wg_commit();
        }
        wg_wait<0>();
        reg_fence16(s);
        TS0(64);
        {
            uint32_t ra, rb;
            asm("mapa.shared::cluster.u32 %0, %1, %2;" : "=r"(ra) : "r"(sb + xo), "r"(rank ^ 1));
            asm("mapa.shared::cluster.u32 %0, %1, %2;" : "=r"(rb) : "r"(bars + (B_X + wg) * 8), "r"(rank ^ 1));
#pragma unroll
            for (int i = 0; i < 4; i++)
                asm volatile("st.async.weak.shared::cluster.mbarrier::complete_tx::bytes.v4.f32 [%0], {%1,%2,%3,%4}, [%5];"
                             ::"r"(ra + i * 2048), "f"(s[4 * i]), "f"(s[4 * i + 1]), "f"(s[4 * i + 2]), "f"(s[4 * i + 3]), "r"(rb) : "memory");
        }
        float4 xs[4];
#define QK_TAIL(c) do { \
            mbar_wait2(bars + (C_T1 + 2 * (c)) * 8); \
            const uint64_t da = mkdesc(sb + S_CKV + (6 + (c)) * 8192), dx = mkdesc(sb + S_XCH + (c) * 8192), db = mkdesc(sb + S_QABS + (2 + (c)) * 4096); \
            wg_fence(); \
            _Pragma("unroll") for (int k = 0; k < 4; k++) { wgmma_n32<0>(s, da + k * 2, db + k * 2, 1); wgmma_n32<0>(s, dx + k * 2, db + 512 + k * 2, 1); } \
            wg_commit(); } while (0)
        if (wg) QK_TAIL(0);
        mbar_wait_cluster(bars + (B_X + wg) * 8);
#pragma unroll
        for (int i = 0; i < 4; i++) xs[i] = lds4f(sb + xo + i * 2048);
        if (wg) QK_TAIL(1);
        wg_wait<0>();
        reg_fence16(s);
        TS4(7); TS0(65);
#pragma unroll
        for (int i = 0; i < 4; i++) { s[4 * i] += xs[i].x; s[4 * i + 1] += xs[i].y; s[4 * i + 2] += xs[i].z; s[4 * i + 3] += xs[i].w; }
        const bool b2 = lane & 16, b1 = lane & 8, b0 = lane & 4;
        {
            float v[8];
#pragma unroll
            for (int i = 0; i < 4; i++) { v[2 * i] = fmaxf(s[4 * i], s[4 * i + 2]); v[2 * i + 1] = fmaxf(s[4 * i + 1], s[4 * i + 3]); }
            float u[4];
#pragma unroll
            for (int k = 0; k < 4; k++) u[k] = fmaxf(b2 ? v[k + 4] : v[k], __shfl_xor_sync(~0u, b2 ? v[k] : v[k + 4], 16));
            float t[2];
#pragma unroll
            for (int k = 0; k < 2; k++) t[k] = fmaxf(b1 ? u[k + 2] : u[k], __shfl_xor_sync(~0u, b1 ? u[k] : u[k + 2], 8));
            const uint32_t r = ordf(__float_as_uint(fmaxf(b0 ? t[1] : t[0], __shfl_xor_sync(~0u, b0 ? t[0] : t[1], 4))));
            const uint32_t a = sb + S_MAX + (8 * (g >> 1) + 2 * q + (g & 1)) * 4;
            red_max(a + 128, r);
            if (wg == 0) red_max(a, r);
        }
        if (wg == 0) { bar_arrive(4, 256); bar_sync(3, 128); } else { bar_arrive(7, 256); bar_sync(4, 256); }
        TS4(66);
        uint32_t pk[8];
#pragma unroll
        for (int i = 0; i < 4; i++) {
            const float2 mm = lds2f(sb + S_MAX + wg * 128 + (8 * i + 2 * q) * 4);
            const float m0 = u2f(ordf(__float_as_uint(mm.x))), m1 = u2f(ordf(__float_as_uint(mm.y)));
            pk[2 * i] = packbf(ex2(s[4 * i] - m0), ex2(s[4 * i + 1] - m1));
            pk[2 * i + 1] = packbf(ex2(s[4 * i + 2] - m0), ex2(s[4 * i + 3] - m1));
        }
        {
            const int t = lane >> 3, r8 = lane & 7;
            const uint32_t a = sb + S_P + wg * 4096 + ((t >> 1) * 8 + r8) * 128 + (((2 * wq + (t & 1)) ^ r8) << 4);
            stsm4t(a, pk[0], pk[1], pk[2], pk[3]);
            stsm4t(a + 2048, pk[4], pk[5], pk[6], pk[7]);
        }
        fence_async();
        TS4(67); TS0(68);
        if (wg) {
            bar_arrive(5, 256);
            if (warp == 4) {
                str1(sp + G_ML + spread(pair * 256 + lane * 4) + rank * 4096, tagf(u2f(ordf(lds1(sb + S_MAX + 128 + lane * 4))), tg));
                if (lane == 0) mbar_arrive(bars + B_QK * 8);
            }
        } else {
            float o0[16], o1[16], o2[16], o3[16], ol[16];
            const uint64_t d1 = mkdesc(sb + S_ONES) & ~(0x3FFFull << 32);
            const uint64_t db = mkdesc(sb + S_P), da = mkdesc(sb + S_CKV);
            bar_sync(3, 128);
            wg_fence();
#pragma unroll
            for (int k = 0; k < 4; k++) {
                wgmma_n32<1>(o0, da + k * 128, db + k * 2, k);
                wgmma_n32<1>(o1, da + 512 + k * 128, db + k * 2, k);
                wgmma_n32<1>(o2, da + 1024 + k * 128, db + k * 2, k);
                wgmma_n32<1>(o3, da + 1536 + k * 128, db + k * 2, k);
                wgmma_n32<0>(ol, d1, db + k * 2, k);
            }
            wg_commit();
            wg_wait<0>();
            reg_fence16(o0); reg_fence16(o1); reg_fence16(o2); reg_fence16(o3); reg_fence16(ol);
            TS0(23);
            bar_sync(7, 256);
            {
                const float al = ex2(u2f(ordf(lds1(sb + S_MAX + lane * 4))) - u2f(ordf(lds1(sb + S_MAX + 128 + lane * 4))));
#pragma unroll
                for (int i = 0; i < 4; i++) {
                    const float a0 = __shfl_sync(~0u, al, 8 * i + 2 * q), a1 = __shfl_sync(~0u, al, 8 * i + 2 * q + 1);
                    o0[4 * i] *= a0; o0[4 * i + 1] *= a1; o0[4 * i + 2] *= a0; o0[4 * i + 3] *= a1;
                    o1[4 * i] *= a0; o1[4 * i + 1] *= a1; o1[4 * i + 2] *= a0; o1[4 * i + 3] *= a1;
                    o2[4 * i] *= a0; o2[4 * i + 1] *= a1; o2[4 * i + 2] *= a0; o2[4 * i + 3] *= a1;
                    o3[4 * i] *= a0; o3[4 * i + 1] *= a1; o3[4 * i + 2] *= a0; o3[4 * i + 3] *= a1;
                    ol[4 * i] *= a0; ol[4 * i + 1] *= a1; ol[4 * i + 2] *= a0; ol[4 * i + 3] *= a1;
                }
            }
            unsigned char* ldst = sp + G_ML + spread(pair * 256 + 128 + wq * 32 + q * 8) + rank * 4096;
            PIN(ldst);
            TS0(81);
            bar_sync(5, 256);
            wg_fence();
#pragma unroll
            for (int k = 0; k < 4; k++) {
                wgmma_n32<1>(o0, da + 2048 + k * 128, db + 256 + k * 2, 1);
                wgmma_n32<1>(o1, da + 2048 + 512 + k * 128, db + 256 + k * 2, 1);
            }
            wg_commit();
            wg_wait<0>();
            reg_fence16(o0); reg_fence16(o1);
            TS0(24);
            wg_fence();
#pragma unroll
            for (int k = 0; k < 4; k++) wgmma_n32<1>(o2, da + 2048 + 1024 + k * 128, db + 256 + k * 2, 1);
            wg_commit();
#define O_STORE(A, B, OFF) _Pragma("unroll") for (int i = 0; i < 4; i++) _Pragma("unroll") for (int e = 0; e < 2; e++) { \
                const float f0 = u2f((__float_as_uint(A[4 * i + e]) + 0x10000u) & 0xFFFE0000u); \
                str64(h4dst + (OFF) + i * 16384 + e * 1024, packbf(f0, A[4 * i + 2 + e]) | tg4w, packbf(B[4 * i + e], B[4 * i + 2 + e])); }
            TS0(8);
            O_STORE(o0, o1, 0);
            __syncwarp();
            wg_fence();
#pragma unroll
            for (int k = 0; k < 4; k++) {
                wgmma_n32<1>(o3, da + 2048 + 1536 + k * 128, db + 256 + k * 2, 1);
                wgmma_n32<0>(ol, d1, db + 256 + k * 2, 1);
            }
            wg_commit();
            wg_wait<0>();
            reg_fence16(o2); reg_fence16(o3); reg_fence16(ol);
            {
                const float l0 = (wq & 2) ? ((wq & 1) ? ol[12] : ol[8]) : ((wq & 1) ? ol[4] : ol[0]);
                const float l1 = (wq & 2) ? ((wq & 1) ? ol[13] : ol[9]) : ((wq & 1) ? ol[5] : ol[1]);
                if (g == 0) str2(ldst, tagf(l0, tg), tagf(l1, tg));
            }
            O_STORE(o2, o3, 64);
            if (lane == 0) mbar_arrive(bars + B_O * 8);
        }
    }
    TS0(9);
    const uint32_t t_o = clk32();
    uint32_t af[8][4];
    {
        const int sg = wq * 4 + (lane >> 3), ur = (lane >> 2) & 1;
        const int po = ur * 128 + (wg ^ 1) * 64 + q * 16;
        uint32_t a0;
        {
            const int m = lane >> 3, r8 = lane & 7;
            const int row = (m >> 1) * 16 + (r8 >> 1) * 2 + (r8 & 1) * 8;
            a0 = sb + S_WUV + wg * 4096 + row * 128 + (((wq * 2 + (m & 1)) ^ (row & 7)) << 4);
        }
        const unsigned char* src[4];
        uint32_t tg4[4];
#pragma unroll
        for (int i = 0; i < 4; i++) {
            const float2 m = lds2f(sb + S_B4 + i * 8);
            src[i] = sp + pick(G_H4 + (sg + 16 * i) * 131072 + spread(b * 256 + po), __float_as_uint(m.x) >> (sg * 2 + ur));
            tg4[i] = __float_as_uint(m.y) >> (sg * 2 + ur);
        }
        uint4 v[4];
        uint32_t have = 0;
        int it = 0;
        unsigned char* d5 = sp + G_H5 + spread(b * 512 + warp * 64 + (q & 1) * 32 + g * 4) + (q >> 1) * 4096;
        PIN(d5);
        if (wg) mbar_wait(bars + B_O * 8);
        wait_until(wg ? clk32() - p.tm[A_H4] : t_o, p.tm[D_H4]);
        wait_until(t_start, p.tm[T_H4] - (wg ? p.tm[A_H4] : 0));
#pragma unroll
        for (int i = 0; i < 4; i++) v[i] = ldr64x2(src[i]);
        TS0(10);
#define LOAD_UV(now) _Pragma("unroll") for (int i = 0; i < 4; i++) \
            if ((now) >> i & 1) { ldsm4t(a0 + i * 8192, af[2 * i]); ldsm4t((a0 + i * 8192 + 128) ^ 16, af[2 * i + 1]); }
        have = mbar_mask4(bars + C_WUV * 8);
        LOAD_UV(have);
        mbar_wait(bars + B_W * 8);
        float wt[4];
#pragma unroll
        for (int i = 0; i < 4; i++) wt[i] = lds1f(sb + S_ML + (sg + 16 * i) * 4);
#pragma unroll 1
        while (__any_sync(~0u, (or3(xo2(v[0].x, v[0].z, tg4[0]), xo2(v[1].x, v[1].z, tg4[1]), xo2(v[2].x, v[2].z, tg4[2])) | xo2(v[3].x, v[3].z, tg4[3])) & 1)) {
#pragma unroll
            for (int i = 0; i < 4; i++) if (xo2(v[i].x, v[i].z, tg4[i]) & 1) v[i] = ldr64x2(src[i]);
            SPIN_CHECK(it);
        }
        float acc[8] = {0.f, 0.f, 0.f, 0.f, 0.f, 0.f, 0.f, 0.f};
#pragma unroll
        for (int i = 0; i < 4; i++) {
            const uint32_t w[4] = {v[i].x & ~1u, v[i].y, v[i].z & ~1u, v[i].w};
#pragma unroll
            for (int k = 0; k < 4; k++) {
                acc[2 * k] = fmaf(wt[i], bflo(w[k]), acc[2 * k]);
                acc[2 * k + 1] = fmaf(wt[i], bfhi(w[k]), acc[2 * k + 1]);
            }
        }
        TS0(25);
        {
            const bool u16 = lane & 16, u8 = lane & 8;
            float r[4];
#pragma unroll
            for (int k = 0; k < 4; k++) r[k] = (u16 ? acc[k + 4] : acc[k]) + __shfl_xor_sync(~0u, u16 ? acc[k] : acc[k + 4], 16);
            const float t0 = (u8 ? r[2] : r[0]) + __shfl_xor_sync(~0u, u8 ? r[0] : r[2], 8);
            const float t1 = (u8 ? r[3] : r[1]) + __shfl_xor_sync(~0u, u8 ? r[1] : r[3], 8);
            uint32_t hi, lo; split2(t0, t1, hi, lo);
            const uint32_t a = sb + S_RED + wq * 320 + po + (u16 ? 8 : 0) + (u8 ? 4 : 0);
            sts1(a, hi); sts1(a + 4 * 320, lo);
        }
        bar_sync(2, 256);
        uint4 bq[4];
#pragma unroll
        for (int i = 0; i < 4; i++) bq[i] = lds4(sb + S_RED + g * 320 + i * 64 + q * 16);
        if (have != 15) { mbar_wait4(bars + C_WUV * 8); LOAD_UV(~have); }
        float d[4][4];
#pragma unroll
        for (int i = 0; i < 4; i++) {
            d[i][0] = d[i][1] = d[i][2] = d[i][3] = 0.f;
            mma16816(d[i], af[2 * i], bq[i].x, bq[i].y);
            mma16816(d[i], af[2 * i + 1], bq[i].z, bq[i].w);
        }
        const float r0 = ((d[0][0] + d[0][1]) + (d[1][0] + d[1][1])) + ((d[2][0] + d[2][1]) + (d[3][0] + d[3][1]));
        const float r1 = ((d[0][2] + d[0][3]) + (d[1][2] + d[1][3])) + ((d[2][2] + d[2][3]) + (d[3][2] + d[3][3]));
        float r = ((q & 1) ? r1 : r0) + __shfl_xor_sync(~0u, (q & 1) ? r0 : r1, 1);
        r += __shfl_xor_sync(~0u, r, 2);
        str1(d5, tagf(r, tg));
    }
    const uint32_t t_e = clk32();
    TS0(12);
    const unsigned char* sm[4];
    uint2 mm[6];
#pragma unroll
    for (int i = 0; i < 4; i++) sm[i] = sp + pick(G_MOD2 + i * 8192 + tid * 8, beta);
#define LOAD_MM() do { mm[0] = ldr2(sm[0]); mm[1] = ldr2(sm[0] + 2048); mm[2] = ldr2(sm[1]); mm[3] = ldr2(sm[2]); mm[4] = ldr2(sm[2] + 2048); mm[5] = ldr2(sm[3]); } while (0)
#define BAD_MM() or3(or3(bad2(mm[0], tg), bad2(mm[1], tg), bad2(mm[2], tg)), or3(bad2(mm[3], tg), bad2(mm[4], tg), bad2(mm[5], tg)), 0)
    {
        const int m = lane >> 3, r8 = lane & 7;
        const uint32_t a0 = sb + S_WO + (warp >> 1) * 2048 + ((m >> 1) * 8 + r8) * 64 + ((((warp & 1) * 2 + (m & 1)) ^ (r8 >> 1)) << 4);
        const unsigned char* src = sp + pick(G_H5 + spread(((b >> 4) * 4 + (warp >> 1)) * 2048 + (tid & 63) * 8), beta);
        uint2 c0, c1, c2, c3; int it = 0;
        uint32_t have = 0;
        unsigned char* d6 = sp + G_H6 + spread(b * 128 + lane * 4) + (warp & 1) * 4096;
        PIN(d6);
        wait_until(t_e, p.tm[D_H5]);
#pragma unroll 1
        do {
            c0 = ldr2(src); c1 = ldr2(src + 512); c2 = ldr2(src + 1024); c3 = ldr2(src + 1536);
            const uint32_t now = mbar_mask4(bars + C_WO * 8) & ~have;
#pragma unroll
            for (int i = 0; i < 4; i++)
                if (now >> i & 1) { ldsm4t(a0 + i * 8192, af[2 * i]); ldsm4t(a0 + i * 8192 + 1024, af[2 * i + 1]); }
            have |= now;
            SPIN_CHECK(it);
        } while (__any_sync(~0u, or3(or3(bad2(c0, tg), bad2(c1, tg), bad2(c2, tg)), bad2(c3, tg), 0) & 1));
        uint32_t hi, lo;
        split2((u2f(c0.x) + u2f(c1.x)) + (u2f(c2.x) + u2f(c3.x)), (u2f(c0.y) + u2f(c1.y)) + (u2f(c2.y) + u2f(c3.y)), hi, lo);
        const uint32_t a = sb + S_FVEC + (tid >> 4) * 128 + vpos((tid & 15) * 2);
        sts1(a, hi); sts1(a + 64, lo);
        TS0(14);
        bar_sync(2, 256);
        if (b < NFFN) LOAD_MM();
        uint4 bq[4];
#pragma unroll
        for (int i = 0; i < 4; i++) bq[i] = lds4(sb + S_FVEC + (i * 4 + (warp >> 1)) * 128 + vlane);
        if (have != 15) {
#pragma unroll
            for (int i = 0; i < 4; i++)
                if (!(have >> i & 1)) {
                    mbar_wait(bars + (C_WO + i) * 8);
                    ldsm4t(a0 + i * 8192, af[2 * i]); ldsm4t(a0 + i * 8192 + 1024, af[2 * i + 1]);
                }
        }
        float d[4][4];
#pragma unroll
        for (int i = 0; i < 4; i++) {
            d[i][0] = d[i][1] = d[i][2] = d[i][3] = 0.f;
            mma16816(d[i], af[2 * i], bq[i].x, bq[i].y);
            mma16816(d[i], af[2 * i + 1], bq[i].z, bq[i].w);
        }
        TS0(15);
        {
            const uint32_t o = sb + (q ? S_RED + tid * 4 : S_R16 + ((warp & 1) * 16 + g) * 16 + (warp >> 1) * 4);
            sts1f(o, ((d[0][0] + d[0][1]) + (d[1][0] + d[1][1])) + ((d[2][0] + d[2][1]) + (d[3][0] + d[3][1])));
            sts1f(o + 128, ((d[0][2] + d[0][3]) + (d[1][2] + d[1][3])) + ((d[2][2] + d[2][3]) + (d[3][2] + d[3][3])));
        }
        bar_sync(2, 256);
        if (tid < 64) {
            const float4 u = lds4f(sb + S_R16 + lane * 16);
            str1(d6, tagf((u.x + u.y) + (u.z + u.w), tg));
        }
        if (tid == 64) mbar_arrive(bars + B_F * 8);
        if (tid >= 224) str4(sp + G_H3 + (j * 2 + ((tid >> 3) & 1)) * 8192 + (tid & 16) * 256 + h * 128 + (tid & 7) * 16, 0, 0, 0, 0);
    }
    const uint32_t t_f = clk32();
    TS0(26);
    if (b < NFFN) {
        const uint32_t ga_ = sb + S_GVEC + (warp * 2 + (lane >> 4)) * 512 + vpos((lane & 15) * 2);
        TS0(16);
        const int m = lane >> 3, r8 = lane & 7;
        const uint32_t a0 = sb + S_W1 + warp * 2048 + ((m >> 1) * 8 + r8) * 32 + (((m & 1) ^ (r8 >> 2)) << 4);
        bool have1 = false;
        unsigned char* d7 = sp + G_H7 + (tid >> 2) * 8192 + b * 32 + (tid & 3) * 8;
        PIN(d7);
        float x20, x21;
        {
            const unsigned char* so[4];
#pragma unroll
            for (int i = 0; i < 4; i++) so[i] = sp + pick(G_H6 + i * 8192 + tid * 8, beta);
            uint2 c[8]; int it = 0;
            float g0, g1;
#define STAGE_MM() do { \
                g0 = 1.f + (u2f(mm[2].x) + u2f(mm[5].x)); g1 = 1.f + (u2f(mm[2].y) + u2f(mm[5].y)); \
                uint32_t hi, lo; \
                split2(g0, g1, hi, lo); sts1(ga_ + 128, hi); sts1(ga_ + 192, lo); \
                split2(u2f(mm[1].x) + u2f(mm[4].x), u2f(mm[1].y) + u2f(mm[4].y), hi, lo); sts1(ga_ + 256, hi); sts1(ga_ + 320, lo); } while (0)
#pragma unroll 1
            while (BAD_MM() & 1) { LOAD_MM(); SPIN_CHECK(it); }
            STAGE_MM();
            have1 = mbar_mask4(bars + C_W1 * 8) >> wg & 1;
            if (have1) {
#pragma unroll
                for (int i = 0; i < 4; i++) ldsm4t(a0 + i * 512, af[i]);
            }
            wait_until(t_f, p.tm[D_H6]);
#pragma unroll 1
            while (true) {
#pragma unroll
                for (int i = 0; i < 8; i++) c[i] = ldr2(so[i >> 1] + (i & 1) * 2048);
                uint32_t bc = 0;
                bc = or3(or3(bad2(c[0], tg), bad2(c[1], tg), bad2(c[2], tg)), or3(bad2(c[3], tg), bad2(c[4], tg), bad2(c[5], tg)),
                         or3(bad2(c[6], tg), bad2(c[7], tg), bc));
                if (!__any_sync(~0u, bc & 1)) break;
                SPIN_CHECK(it);
            }
            x20 = fmaf(u2f(mm[0].x) + u2f(mm[3].x),
                       ((u2f(c[0].x) + u2f(c[1].x)) + (u2f(c[2].x) + u2f(c[3].x))) + ((u2f(c[4].x) + u2f(c[5].x)) + (u2f(c[6].x) + u2f(c[7].x))), bflo(xw2));
            x21 = fmaf(u2f(mm[0].y) + u2f(mm[3].y),
                       ((u2f(c[0].y) + u2f(c[1].y)) + (u2f(c[2].y) + u2f(c[3].y))) + ((u2f(c[4].y) + u2f(c[5].y)) + (u2f(c[6].y) + u2f(c[7].y))), bfhi(xw2));
            uint32_t hi, lo;
            split2(x20 * g0, x21 * g1, hi, lo); sts1(ga_, hi); sts1(ga_ + 64, lo);
            split2(x20, x21, hi, lo); sts1(ga_ + 384, hi); sts1(ga_ + 448, lo);
            if ((tid >> 2) == b) sts2(sb + S_X2 + (tid & 3) * 8, __float_as_uint(x20), __float_as_uint(x21));
        }
        TS0(17);
        __syncwarp();
        const uint32_t va = sb + S_GVEC + warp * 1024 + g * 64 + q * 16;
        const uint4 bq0 = lds4(va), bq1 = lds4(va + 512);
        if (!have1) {
            mbar_wait(bars + (C_W1 + wg) * 8);
#pragma unroll
            for (int i = 0; i < 4; i++) ldsm4t(a0 + i * 512, af[i]);
        }
        float d0[4] = {0.f, 0.f, 0.f, 0.f}, d1[4] = {0.f, 0.f, 0.f, 0.f}, d2[4] = {0.f, 0.f, 0.f, 0.f}, d3[4] = {0.f, 0.f, 0.f, 0.f};
        mma16816(d0, af[0], bq0.x, bq0.y); mma16816(d1, af[1], bq0.z, bq0.w);
        mma16816(d2, af[2], bq1.x, bq1.y); mma16816(d3, af[3], bq1.z, bq1.w);
        float e0[4] = {0.f, 0.f, 0.f, 0.f}, e1[4] = {0.f, 0.f, 0.f, 0.f};
        {
            const uint32_t one = 0x3F803F80u;
            const uint32_t t0[4] = {bq0.x, one, bq0.y, one}, t1[4] = {bq0.z, one, bq0.w, one};
            const uint32_t t2[4] = {bq1.x, one, bq1.y, one}, t3[4] = {bq1.z, one, bq1.w, one};
            mma16816(e0, t0, bq0.x, bq0.y); mma16816(e1, t1, bq0.z, bq0.w);
            mma16816(e0, t2, bq1.x, bq1.y); mma16816(e1, t3, bq1.z, bq1.w);
        }
        {
            const bool st = q == 3;
            const float lo_ = fsel(st, (e0[0] + e0[1]) + (e1[0] + e1[1]), ((d0[0] + d0[1]) + (d1[0] + d1[1])) + ((d2[0] + d2[1]) + (d3[0] + d3[1])));
            const float hi_ = fsel(st, (e0[2] + e0[3]) + (e1[2] + e1[3]), ((d0[2] + d0[3]) + (d1[2] + d1[3])) + ((d2[2] + d2[3]) + (d3[2] + d3[3])));
            sts1f(sb + S_RED + q * 512 + g * 32 + warp * 4, lo_);
            sts1f(sb + S_RED + q * 512 + (g + 8) * 32 + warp * 4, hi_);
        }
        TS0(18);
        bar_arrive(9, 288);
        uint32_t w2r[16];
        mbar_wait2(bars + C_W2 * 8);
#pragma unroll
        for (int r = 0; r < 16; r++) w2r[r] = lds1(sb + S_W2 + r * 1024 + tid * 4);
        float w2f[32];
#pragma unroll
        for (int r = 0; r < 16; r++) { w2f[2 * r] = bflo(w2r[r]); w2f[2 * r + 1] = bfhi(w2r[r]); }
        bar_sync(10, b < 64 ? 320 : 288);
        float y0a = 0.f, y0b = 0.f, y1a = 0.f, y1b = 0.f;
#pragma unroll
        for (int r = 0; r < 16; r += 4) {
            const float4 f = lds4f(sb + S_STAT + r * 4);
            y0a = fmaf(f.x, w2f[2 * r], y0a); y1a = fmaf(f.x, w2f[2 * r + 1], y1a);
            y0b = fmaf(f.y, w2f[2 * r + 2], y0b); y1b = fmaf(f.y, w2f[2 * r + 3], y1b);
            y0a = fmaf(f.z, w2f[2 * r + 4], y0a); y1a = fmaf(f.z, w2f[2 * r + 5], y1a);
            y0b = fmaf(f.w, w2f[2 * r + 6], y0b); y1b = fmaf(f.w, w2f[2 * r + 7], y1b);
        }
        const uint32_t w0 = tagf(y0a + y0b, tg), w1 = tagf(y1a + y1b, tg);
        str2(d7, w0, w1); str2(d7 + 4096, w0, w1);
        TS0(19);
    }
}

__global__ void fb_gemv(const float* v, int vs, const __nv_bfloat16* W, size_t ws, size_t ks, size_t ns, int K, int N, float* out, float scale) {
    const int n = blockIdx.x * 8 + (threadIdx.x >> 5), z = blockIdx.y;
    if (n >= N) return;
    float s = 0.f;
    for (int k = threadIdx.x & 31; k < K; k += 32) s += v[(size_t)z * vs + k] * __bfloat162float(W[z * ws + k * ks + n * ns]);
    for (int o = 16; o; o >>= 1) s += __shfl_xor_sync(~0u, s, o);
    if ((threadIdx.x & 31) == 0) out[(size_t)z * N + n] = s * scale;
}
__device__ float fb_block_reduce(float v, bool mx, float* sh) {
    for (int o = 16; o; o >>= 1) { const float t = __shfl_xor_sync(~0u, v, o); v = mx ? fmaxf(v, t) : v + t; }
    __syncthreads();
    if ((threadIdx.x & 31) == 0) sh[threadIdx.x >> 5] = v;
    __syncthreads();
    v = sh[0];
    for (int i = 1; i < 16; i++) v = mx ? fmaxf(v, sh[i]) : v + sh[i];
    return v;
}
__global__ void fb_elem(int step, Params p, float* f) {
    __shared__ float sh[16];
    const int t = threadIdx.x;
    float* sc = f; float* mod = f + 512; float* hh = f + 4096; float* sco = f + 32768; float* o = f + 8192; float* x2 = f + 8704;
    float* ff = f + 9216; float* y = f + 11264;
    if (step == 0) { const float c = __bfloat162float(p.c[t]); sc[t] = c / (1.f + expf(-c)); }
    if (step == 1 || step == 3) {
        float x = __bfloat162float(p.x[t]);
        if (step == 3) { x += mod[1024 + t] * o[t]; x2[t] = x; }
        const float m = fb_block_reduce(x, false, sh) / 512.f, va = fb_block_reduce((x - m) * (x - m), false, sh) / 512.f;
        hh[t] = (x - m) * rsqrtf(va + 1e-5f) * (1.f + mod[(step == 1 ? 512 : 2048) + t]) + mod[(step == 1 ? 0 : 1536) + t];
    }
    if (step == 2) {
        float* r = sco + blockIdx.x * 8192;
        float m = -INFINITY, s = 0.f;
        for (int k = t; k < 8192; k += 512) m = fmaxf(m, r[k]);
        m = fb_block_reduce(m, true, sh);
        for (int k = t; k < 8192; k += 512) { r[k] = expf(r[k] - m); s += r[k]; }
        s = fb_block_reduce(s, false, sh);
        for (int k = t; k < 8192; k += 512) r[k] /= s;
    }
    if (step == 4)
        for (int n = t; n < 1376; n += 512) {
            const float a = ff[n] + __bfloat162float(p.b1[n]);
            ff[n] = 0.5f * a * (1.f + tanhf(0.7978845608f * (a + 0.044715f * a * a * a)));
        }
    if (step == 5) p.out[t] = __float2bfloat16(x2[t] + mod[2560 + t] * (y[t] + __bfloat162float(p.b2[t])));
}
void launch_fallback(const Params& p, void* const* d_in, cudaStream_t st) {
    typedef const __nv_bfloat16* W;
    float* f = reinterpret_cast<float*>(p.s + G_BYTES - (2 << 20) + 0);
    float *sc = f, *mod = f + 512, *hh = f + 4096, *q = f + 12288, *qa = f + 16384, *sco = f + 32768, *cc = f + 16384, *ctx = f + 12288;
    float *o = f + 8192, *ff = f + 9216, *y = f + 11264;
    fb_elem<<<1, 512, 0, st>>>(0, p, f);
    fb_gemv<<<dim3(384, 1), 256, 0, st>>>(sc, 0, (W)d_in[12], 0, 3072, 1, 512, 3072, mod, 1.f);
    fb_elem<<<1, 512, 0, st>>>(1, p, f);
    fb_gemv<<<dim3(512, 1), 256, 0, st>>>(hh, 0, (W)d_in[2], 0, 4096, 1, 512, 4096, q, 1.f);
    fb_gemv<<<dim3(64, 32), 256, 0, st>>>(q, 128, (W)d_in[3], 128, 1, 4096, 128, 512, qa, 0.08838834764831845f);
    fb_gemv<<<dim3(1024, 32), 256, 0, st>>>(qa, 512, (W)d_in[1], 0, 1, 512, 512, 8192, sco, 1.f);
    fb_elem<<<32, 512, 0, st>>>(2, p, f);
    fb_gemv<<<dim3(64, 32), 256, 0, st>>>(sco, 8192, (W)d_in[1], 0, 512, 1, 8192, 512, cc, 1.f);
    fb_gemv<<<dim3(16, 32), 256, 0, st>>>(cc, 512, (W)d_in[4], 128, 4096, 1, 512, 128, ctx, 1.f);
    fb_gemv<<<dim3(64, 1), 256, 0, st>>>(ctx, 0, (W)d_in[5], 0, 512, 1, 4096, 512, o, 1.f);
    fb_elem<<<1, 512, 0, st>>>(3, p, f);
    fb_gemv<<<dim3(172, 1), 256, 0, st>>>(hh, 0, (W)d_in[7], 0, 1376, 1, 512, 1376, ff, 1.f);
    fb_elem<<<1, 512, 0, st>>>(4, p, f);
    fb_gemv<<<dim3(64, 1), 256, 0, st>>>(ff, 0, (W)d_in[9], 0, 512, 1, 1376, 512, y, 1.f);
    fb_elem<<<1, 512, 0, st>>>(5, p, f);
}

typedef CUresult (*EncodeFn)(CUtensorMap*, CUtensorMapDataType, cuuint32_t, void*, const cuuint64_t*, const cuuint64_t*,
                             const cuuint32_t*, const cuuint32_t*, CUtensorMapInterleave, CUtensorMapSwizzle,
                             CUtensorMapL2promotion, CUtensorMapFloatOOBfill);

void make_map(EncodeFn enc, CUtensorMap* m, const void* ptr, uint64_t d0, uint64_t d1, uint64_t d2, uint64_t d3,
              uint64_t s1, uint64_t s2, uint64_t s3, uint32_t b0, uint32_t b1, uint32_t b2, uint32_t b3, CUtensorMapSwizzle sw) {
    cuuint64_t dims[4] = {d0, d1, d2, d3};
    cuuint64_t st[3] = {s1, s2, s3};
    cuuint32_t box[4] = {b0, b1, b2, b3};
    cuuint32_t es[4] = {1, 1, 1, 1};
    enc(m, CU_TENSOR_MAP_DATA_TYPE_BFLOAT16, 4, const_cast<void*>(ptr), dims, st, box, es, CU_TENSOR_MAP_INTERLEAVE_NONE, sw,
        CU_TENSOR_MAP_L2_PROMOTION_L2_128B, CU_TENSOR_MAP_FLOAT_OOB_FILL_NONE);
}

uint16_t g_tm[NTM] = {3830,7720,14652,330,200,650,700,210};
uint16_t g_sched[34] = {0,1120,1696,2272,2848,3424,4060,4636,5212,5788,6364,6940,7516,8092,8668,9184,9184,
                        9722,9892,9932,10232,10912,12422,12812,14762,14782,14802,16422,16992,18032,18162,19132,19172,0};

}

extern "C" void kernel_launch(void* const* d_in, const int* in_sizes, int n_in, void* d_out, int out_size) {
    (void)in_sizes; (void)n_in; (void)out_size;
    static EncodeFn enc = nullptr;
    static unsigned char* scratch = nullptr;
    static bool fused_ok = false;
    if (!scratch) {
        cudaGetSymbolAddress((void**)&scratch, g_scratch);
        scratch = (unsigned char*)(((uintptr_t)scratch + (2 << 20) - 1) & ~(uintptr_t)((2 << 20) - 1));
        void* fn = nullptr;
        cudaDriverEntryPointQueryResult qr;
        cudaGetDriverEntryPoint("cuTensorMapEncodeTiled", &fn, cudaEnableDefault, &qr);
        enc = (EncodeFn)fn;
        int clusters = 0;
        if (enc && cudaFuncSetAttribute(fused_decode_kernel, cudaFuncAttributeMaxDynamicSharedMemorySize, SMEM_BYTES) == cudaSuccess) {
            cudaLaunchConfig_t cfg = {};
            cfg.gridDim = dim3(NCTA); cfg.blockDim = dim3(NTHR); cfg.dynamicSmemBytes = SMEM_BYTES;
            cudaLaunchAttribute at[1];
            at[0].id = cudaLaunchAttributeClusterDimension; at[0].val.clusterDim.x = 2; at[0].val.clusterDim.y = 1; at[0].val.clusterDim.z = 1;
            cfg.attrs = at; cfg.numAttrs = 1;
            if (cudaOccupancyMaxActiveClusters(&clusters, fused_decode_kernel, &cfg) != cudaSuccess) clusters = 0;
        }
        (void)cudaGetLastError();
        fused_ok = clusters >= NCTA / 2;
    }
    Params p = {};
    p.x = (const __nv_bfloat16*)d_in[0];
    p.c = (const __nv_bfloat16*)d_in[11];
    p.b1 = (const __nv_bfloat16*)d_in[8];
    p.b2 = (const __nv_bfloat16*)d_in[10];
    p.out = (__nv_bfloat16*)d_out;
    p.s = scratch;
    for (int i = 0; i < NTM; i++) p.tm[i] = g_tm[i];
    for (int i = 0; i < 34; i++) p.sched[i] = g_sched[i];
    if (!fused_ok) { launch_fallback(p, d_in, cudaStreamPerThread); return; }
    const auto S128 = CU_TENSOR_MAP_SWIZZLE_128B, S32 = CU_TENSOR_MAP_SWIZZLE_32B, S64 = CU_TENSOR_MAP_SWIZZLE_64B, S0 = CU_TENSOR_MAP_SWIZZLE_NONE;
    make_map(enc, &p.m[0], d_in[12], 3072, 512, 1, 1, 6144, 6144 * 512, 6144 * 512, 16, 256, 1, 1, S32);
    make_map(enc, &p.m[1], d_in[2], 64, 512, 64, 1, 8192, 128, 8192 * 512, 64, 32, 2, 1, S128);
    make_map(enc, &p.m[2], d_in[3], 64, 512, 64, 1, 8192, 128, 8192 * 512, 64, 32, 2, 1, S128);
    make_map(enc, &p.m[3], d_in[1], 64, 8192, 8, 1, 1024, 128, 1024 * 8192, 64, 64, 1, 1, S128);
    make_map(enc, &p.m[4], d_in[4], 64, 64, 8, 64, 8192, 8192 * 64, 128, 64, 16, 2, 2, S128);
    make_map(enc, &p.m[5], d_in[5], 512, 4096, 1, 1, 1024, 1024 * 4096, 1024 * 4096, 32, 128, 1, 1, S64);
    make_map(enc, &p.m[8], d_in[12], 3072, 512, 1, 1, 6144, 6144 * 512, 6144 * 512, 32, 128, 1, 1, S64);
    make_map(enc, &p.m[6], d_in[7], 1376, 512, 1, 1, 2752, 2752 * 512, 2752 * 512, 16, 256, 1, 1, S32);
    make_map(enc, &p.m[7], d_in[9], 256, 2752, 1, 1, 512, 512 * 2752, 512 * 2752, 256, 16, 1, 1, S0);
    fused_decode_kernel<<<NCTA, NTHR, SMEM_BYTES, cudaStreamPerThread>>>(p);
}
```

```cpp
#include <cuda_runtime.h>
#include <cuda_bf16.h>
#include <cuda.h>
#include <stdint.h>

namespace {

constexpr int NCTA   = 128;
constexpr int NFFN   = 86;
constexpr int NCHUNK = 33;
constexpr int NTHR   = 384;

constexpr int C_MOD1 = 0, C_WQ = 1, C_WUK = 5, C_CKV = 9, C_T1 = 15, C_WUV = 19, C_W1 = 29, C_W2 = 31;
constexpr int C_MOD2 = 23, C_WO = 25;

constexpr int S_WQ   = 0;
constexpr int S_WUK  = 32768;
constexpr int S_CKV  = 65536;
constexpr int S_WUV  = 131072;
constexpr int S_WO   = 163840;
constexpr int S_MOD2 = 196608;
constexpr int S_MOD1 = 212992;
constexpr int S_SC   = 221184;
constexpr int S_RED  = 223232;
constexpr int S_VEC  = 227328;
constexpr int S_R16  = 227840;
constexpr int S_MAX  = 228352;
constexpr int S_ONES = 229376;
constexpr int S_ML   = 230400;
constexpr int S_X2   = 230400 + 384;
constexpr int S_STAT = 230912;
constexpr int S_BAR  = 230976;
constexpr int S_EP   = 231312;
constexpr int S_B4   = 230912;
constexpr int S_TS   = 231328;
constexpr int S_END  = 231712;
constexpr int S_QABS = S_WQ, S_XBUF1 = S_WQ + 24576, S_XBUF0 = S_MOD1, S_XCH = S_WUK, S_GVEC = S_WQ, S_FVEC = S_WQ + 8192;
constexpr int S_W1 = S_WUK, S_W2 = S_WUK + 16384, S_P = S_MOD1;
constexpr int B_UK = 33, B_QK = 34, B_X = 35, B_F = 37, B_BETA = 38, B_BETA4 = 39, B_W = 40, B_O = 41, NBAR = 42;
constexpr int SMEM_BYTES = S_END;

#define WARM 120
#define WARM_T0 4200
constexpr int WIN = 5;
enum { T_H1 = 0, T_H3, T_H4, D_H5, D_H6, D_H7, D_H4, A_H4, NTM = 8 };

constexpr uint32_t G_H1 = 0;
constexpr uint32_t G_H6 = 192 << 10;
constexpr uint32_t G_MOD2 = 16 << 10;
constexpr uint32_t G_ML = 48 << 10;
constexpr uint32_t G_PROBE = 88 << 10;
constexpr uint32_t G_H3 = 128 << 10;
constexpr uint32_t G_H2 = 256 << 10;
constexpr uint32_t G_H5 = 384 << 10;
constexpr uint32_t G_H7 = 512 << 10;
constexpr uint32_t G_EPOCH = 1 << 20;
constexpr uint32_t G_TS = (1 << 20) + 4096;
constexpr uint32_t G_H4 = 2 << 20;
constexpr uint32_t G_BYTES = 10 << 20;
__device__ __align__(256) unsigned char g_scratch[G_BYTES + (2 << 20)];
__device__ __forceinline__ uint32_t spread(uint32_t o) { return o + (o & ~4095u); }
__device__ __forceinline__ uint32_t pick(uint32_t po, uint32_t beta) {
    return po + (((beta ^ __popc(po & 0xB2000u)) & 1u) << 12);
}
#define TS(i) do {} while (0)
#define TS0(i) do {} while (0)
#define TS4(i) do {} while (0)

struct Params {
    const __nv_bfloat16* x;
    const __nv_bfloat16* c;
    const __nv_bfloat16* b1;
    const __nv_bfloat16* b2;
    __nv_bfloat16* out;
    unsigned char* s;
    uint16_t tm[NTM];
    uint16_t sched[34];
    CUtensorMap m[9];
};

constexpr uint64_t POL_FIRST = 0x12F0000000000000ull, POL_NORMAL = 0x16F0000000000000ull;
constexpr int SPIN_MAX = 1 << 21;

__device__ __forceinline__ void mbar_init(uint32_t bar, uint32_t cnt) {
    asm volatile("mbarrier.init.shared::cta.b64 [%0], %1;" ::"r"(bar), "r"(cnt) : "memory");
}
__device__ __forceinline__ void mbar_expect_tx(uint32_t bar, uint32_t bytes) {
    asm volatile("mbarrier.arrive.expect_tx.shared::cta.b64 _, [%0], %1;" ::"r"(bar), "r"(bytes) : "memory");
}
__device__ __forceinline__ void mbar_arrive(uint32_t bar) {
    asm volatile("mbarrier.arrive.shared::cta.b64 _, [%0];" ::"r"(bar) : "memory");
}
__device__ __forceinline__ void mbar_wait(uint32_t bar) {
    asm volatile("{\n.reg .pred p;\nW:\nmbarrier.try_wait.parity.shared::cta.b64 p, [%0], 0;\n@!p bra W;\n}" ::"r"(bar) : "memory");
}
__device__ __forceinline__ void mbar_wait2(uint32_t bar) {
    asm volatile("{\n.reg .pred p, q;\nW:\n"
                 "mbarrier.try_wait.parity.shared::cta.b64 p, [%0], 0;\n"
                 "mbarrier.try_wait.parity.shared::cta.b64 q, [%0+8], 0;\n"
                 "and.pred p, p, q;\n@!p bra W;\n}" ::"r"(bar) : "memory");
}
__device__ __forceinline__ void mbar_wait4(uint32_t bar) {
    asm volatile("{\n.reg .pred p, q, r, s;\nW:\n"
                 "mbarrier.try_wait.parity.shared::cta.b64 p, [%0], 0;\n"
                 "mbarrier.try_wait.parity.shared::cta.b64 q, [%0+8], 0;\n"
                 "mbarrier.try_wait.parity.shared::cta.b64 r, [%0+16], 0;\n"
                 "mbarrier.try_wait.parity.shared::cta.b64 s, [%0+24], 0;\n"
                 "and.pred p, p, q;\nand.pred r, r, s;\nand.pred p, p, r;\n@!p bra W;\n}" ::"r"(bar) : "memory");
}
__device__ __forceinline__ void mbar_wait_cluster(uint32_t bar) {
    asm volatile("{\n.reg .pred p;\nW:\nmbarrier.try_wait.parity.acquire.cluster.shared::cta.b64 p, [%0], 0;\n@!p bra W;\n}" ::"r"(bar) : "memory");
}
__device__ __forceinline__ void tma4(uint32_t dst, const CUtensorMap* m, int c0, int c1, int c2, int c3, uint32_t bar, uint64_t pol) {
    asm volatile("cp.async.bulk.tensor.4d.shared::cluster.global.mbarrier::complete_tx::bytes.L2::cache_hint [%0], [%1, {%3,%4,%5,%6}], [%2], %7;"
                 ::"r"(dst), "l"(m), "r"(bar), "r"(c0), "r"(c1), "r"(c2), "r"(c3), "l"(pol) : "memory");
}
__device__ __forceinline__ void bar_sync(int id, int n) { asm volatile("bar.sync %0, %1;" ::"r"(id), "r"(n) : "memory"); }
__device__ __forceinline__ void bar_arrive(int id, int n) { asm volatile("bar.arrive %0, %1;" ::"r"(id), "r"(n) : "memory"); }
__device__ __forceinline__ void fence_async() { asm volatile("fence.proxy.async.shared::cta;" ::: "memory"); }

__device__ __forceinline__ uint32_t ldr1(const void* p) {
    uint32_t v; asm volatile("ld.relaxed.gpu.global.u32 %0, [%1];" : "=r"(v) : "l"(p) : "memory"); return v;
}
__device__ __forceinline__ uint2 ldr2(const void* p) {
    uint2 v; asm volatile("ld.relaxed.gpu.global.v2.u32 {%0,%1}, [%2];" : "=r"(v.x), "=r"(v.y) : "l"(p) : "memory"); return v;
}
__device__ __forceinline__ uint4 ldr4(const void* p) {
    uint4 v; asm volatile("ld.relaxed.gpu.global.v4.u32 {%0,%1,%2,%3}, [%4];"
                          : "=r"(v.x), "=r"(v.y), "=r"(v.z), "=r"(v.w) : "l"(p) : "memory"); return v;
}
__device__ __forceinline__ void str1(void* p, uint32_t v) { asm volatile("st.relaxed.gpu.global.u32 [%0], %1;" ::"l"(p), "r"(v) : "memory"); }
__device__ __forceinline__ void str2(void* p, uint32_t a, uint32_t b) {
    asm volatile("st.relaxed.gpu.global.v2.u32 [%0], {%1,%2};" ::"l"(p), "r"(a), "r"(b) : "memory");
}
__device__ __forceinline__ void str4(void* p, uint32_t a, uint32_t b, uint32_t c, uint32_t d) {
    asm volatile("st.relaxed.gpu.global.v4.u32 [%0], {%1,%2,%3,%4};" ::"l"(p), "r"(a), "r"(b), "r"(c), "r"(d) : "memory");
}
__device__ __forceinline__ void str64(void* p, uint32_t a, uint32_t b) {
    asm volatile("{\n.reg .b64 t;\nmov.b64 t, {%1,%2};\nst.relaxed.gpu.global.b64 [%0], t;\n}" ::"l"(p), "r"(a), "r"(b) : "memory");
}
__device__ __forceinline__ uint4 ldr64x2(const void* p) {
    uint4 v; asm volatile("{\n.reg .b64 s, t;\nld.relaxed.gpu.global.v2.b64 {s,t}, [%4];\nmov.b64 {%0,%1}, s;\nmov.b64 {%2,%3}, t;\n}"
                          : "=r"(v.x), "=r"(v.y), "=r"(v.z), "=r"(v.w) : "l"(p) : "memory"); return v;
}
__device__ __forceinline__ uint32_t tagf(float v, uint32_t tg) {
    uint32_t r; asm("lop3.b32 %0, %1, 0xFFFFFFFE, %2, 0xEA;" : "=r"(r) : "r"(__float_as_uint(v)), "r"(tg)); return r;
}
__device__ __forceinline__ float u2f(uint32_t v) { return __uint_as_float(v); }

__device__ __forceinline__ void sts1(uint32_t a, uint32_t v) { asm volatile("st.shared.u32 [%0], %1;" ::"r"(a), "r"(v) : "memory"); }
__device__ __forceinline__ void sts1f(uint32_t a, float v) { asm volatile("st.shared.f32 [%0], %1;" ::"r"(a), "f"(v) : "memory"); }
__device__ __forceinline__ void stsh(uint32_t a, uint32_t v) { asm volatile("st.shared.u16 [%0], %1;" ::"r"(a), "h"((unsigned short)v) : "memory"); }
__device__ __forceinline__ void sts2(uint32_t a, uint32_t x, uint32_t y) { asm volatile("st.shared.v2.u32 [%0], {%1,%2};" ::"r"(a), "r"(x), "r"(y) : "memory"); }
__device__ __forceinline__ void sts4(uint32_t a, uint32_t x, uint32_t y, uint32_t z, uint32_t w) {
    asm volatile("st.shared.v4.u32 [%0], {%1,%2,%3,%4};" ::"r"(a), "r"(x), "r"(y), "r"(z), "r"(w) : "memory");
}
__device__ __forceinline__ uint32_t lds1(uint32_t a) { uint32_t v; asm volatile("ld.shared.u32 %0, [%1];" : "=r"(v) : "r"(a) : "memory"); return v; }
__device__ __forceinline__ float lds1f(uint32_t a) { float v; asm volatile("ld.shared.f32 %0, [%1];" : "=f"(v) : "r"(a) : "memory"); return v; }
__device__ __forceinline__ float2 lds2f(uint32_t a) { float2 v; asm volatile("ld.shared.v2.f32 {%0,%1}, [%2];" : "=f"(v.x), "=f"(v.y) : "r"(a) : "memory"); return v; }
__device__ __forceinline__ uint4 lds4(uint32_t a) {
    uint4 v; asm volatile("ld.shared.v4.u32 {%0,%1,%2,%3}, [%4];" : "=r"(v.x), "=r"(v.y), "=r"(v.z), "=r"(v.w) : "r"(a) : "memory"); return v;
}
__device__ __forceinline__ float4 lds4f(uint32_t a) {
    float4 v; asm volatile("ld.shared.v4.f32 {%0,%1,%2,%3}, [%4];" : "=f"(v.x), "=f"(v.y), "=f"(v.z), "=f"(v.w) : "r"(a) : "memory"); return v;
}
__device__ __forceinline__ void ldsm4(uint32_t a, uint32_t (&r)[4]) {
    asm volatile("ldmatrix.sync.aligned.m8n8.x4.shared.b16 {%0,%1,%2,%3}, [%4];"
                 : "=r"(r[0]), "=r"(r[1]), "=r"(r[2]), "=r"(r[3]) : "r"(a) : "memory");
}
__device__ __forceinline__ void ldsm4t(uint32_t a, uint32_t (&r)[4]) {
    asm volatile("ldmatrix.sync.aligned.m8n8.x4.trans.shared.b16 {%0,%1,%2,%3}, [%4];"
                 : "=r"(r[0]), "=r"(r[1]), "=r"(r[2]), "=r"(r[3]) : "r"(a) : "memory");
}
__device__ __forceinline__ void stsm4t(uint32_t a, uint32_t r0, uint32_t r1, uint32_t r2, uint32_t r3) {
    asm volatile("stmatrix.sync.aligned.m8n8.x4.trans.shared.b16 [%0], {%1,%2,%3,%4};"
                 ::"r"(a), "r"(r0), "r"(r1), "r"(r2), "r"(r3) : "memory");
}
__device__ __forceinline__ void mma16816(float (&d)[4], const uint32_t (&a)[4], uint32_t b0, uint32_t b1) {
    asm volatile("mma.sync.aligned.m16n8k16.row.col.f32.bf16.bf16.f32 {%0,%1,%2,%3}, {%4,%5,%6,%7}, {%8,%9}, {%0,%1,%2,%3};"
                 : "+f"(d[0]), "+f"(d[1]), "+f"(d[2]), "+f"(d[3])
                 : "r"(a[0]), "r"(a[1]), "r"(a[2]), "r"(a[3]), "r"(b0), "r"(b1));
}
__device__ __forceinline__ uint32_t packbf(float lo, float hi) {
    uint32_t r; asm("cvt.rn.bf16x2.f32 %0, %1, %2;" : "=r"(r) : "f"(hi), "f"(lo)); return r;
}
__device__ __forceinline__ float bflo(uint32_t w) { return __uint_as_float(w << 16); }
__device__ __forceinline__ float bfhi(uint32_t w) { return __uint_as_float(w & 0xffff0000u); }
__device__ __forceinline__ void split2(float a, float b, uint32_t& hi, uint32_t& lo) {
    hi = packbf(a, b);
    lo = packbf(a - bflo(hi), b - bfhi(hi));
}
__device__ __forceinline__ uint32_t ordf(uint32_t u) { return u ^ ((uint32_t)((int)u >> 31) & 0x7FFFFFFFu); }
__device__ __forceinline__ void red_max(uint32_t a, uint32_t v) { asm volatile("red.shared.max.s32 [%0], %1;" ::"r"(a), "r"(v) : "memory"); }
__device__ __forceinline__ float fsel(bool c, float a, float b) {
    float r; asm("{\n.reg .pred p;\nsetp.ne.b32 p, %3, 0;\nselp.f32 %0, %1, %2, p;\n}" : "=f"(r) : "f"(a), "f"(b), "r"((int)c)); return r;
}
__device__ __forceinline__ float ex2(float x) { float y; asm("ex2.approx.ftz.f32 %0, %1;" : "=f"(y) : "f"(x)); return y; }

__device__ __forceinline__ int vpos(int k32) {
    return (((k32 & 7) >> 1) * 8 + (k32 >> 4) * 4 + ((k32 >> 3) & 1) * 2 + (k32 & 1)) * 2;
}

__device__ __forceinline__ void wg_fence()  { asm volatile("wgmma.fence.sync.aligned;" ::: "memory"); }
__device__ __forceinline__ void wg_commit() { asm volatile("wgmma.commit_group.sync.aligned;" ::: "memory"); }
template <int N> __device__ __forceinline__ void wg_wait() { asm volatile("wgmma.wait_group.sync.aligned %0;" ::"n"(N) : "memory"); }
__device__ __forceinline__ uint64_t mkdesc(uint32_t addr) {
    return (uint64_t)((addr & 0x3FFFF) >> 4) | ((uint64_t)64 << 16) | ((uint64_t)64 << 32) | ((uint64_t)1 << 62);
}
template <int TA>
__device__ __forceinline__ void wgmma_n32(float (&d)[16], uint64_t da, uint64_t db, int acc) {
    asm volatile("{\n.reg .pred p;\nsetp.ne.b32 p, %18, 0;\n"
                 "wgmma.mma_async.sync.aligned.m64n32k16.f32.bf16.bf16 "
                 "{%0,%1,%2,%3,%4,%5,%6,%7,%8,%9,%10,%11,%12,%13,%14,%15}, %16, %17, p, 1, 1, %19, 0;\n}"
                 : "+f"(d[0]), "+f"(d[1]), "+f"(d[2]), "+f"(d[3]), "+f"(d[4]), "+f"(d[5]), "+f"(d[6]), "+f"(d[7]),
                   "+f"(d[8]), "+f"(d[9]), "+f"(d[10]), "+f"(d[11]), "+f"(d[12]), "+f"(d[13]), "+f"(d[14]), "+f"(d[15])
                 : "l"(da), "l"(db), "r"(acc), "n"(TA));
}
__device__ __forceinline__ void reg_fence16(float (&d)[16]) {
#pragma unroll
    for (int i = 0; i < 16; i++) asm volatile("" : "+f"(d[i])::"memory");
}

template <bool TRANS>
__device__ __forceinline__ void gemv128(uint32_t tile, uint32_t vec, uint32_t bars, int warp, int lane, float& r0, float& r1) {
    const int m = lane >> 3, r8 = lane & 7;
    uint32_t bq[4][4];
#pragma unroll
    for (int i = 0; i < 4; i++) {
        uint4 t = lds4(vec + i * 128 + ((lane >> 2) & 1) * 64 + (lane & 3) * 16);
        bq[i][0] = t.x; bq[i][1] = t.y; bq[i][2] = t.z; bq[i][3] = t.w;
    }
    float d0[4] = {0.f, 0.f, 0.f, 0.f}, d1[4] = {0.f, 0.f, 0.f, 0.f};
    if (TRANS) {
        const uint32_t a0 = tile + (warp >> 2) * 4096 + ((m >> 1) * 8 + r8) * 128 + ((((warp & 3) * 2 + (m & 1)) ^ r8) << 4);
#pragma unroll
        for (int i = 0; i < 4; i++) {
            mbar_wait(bars + i * 8);
            uint32_t a[4], c[4];
            ldsm4t(a0 + i * 8192, a);
            ldsm4t(a0 + i * 8192 + 2048, c);
            mma16816(d0, a, bq[i][0], bq[i][1]);
            mma16816(d1, c, bq[i][2], bq[i][3]);
        }
    } else {
        mbar_wait(bars + (warp >> 1) * 8);
        const uint32_t a0 = tile + (warp >> 1) * 8192 + ((warp & 1) * 16 + (m & 1) * 8 + r8) * 128;
#pragma unroll
        for (int i = 0; i < 4; i++) {
            uint32_t a[4], c[4];
            ldsm4(a0 + (i >> 1) * 4096 + ((((i & 1) * 4 + (m >> 1)) ^ r8) << 4), a);
            ldsm4(a0 + (i >> 1) * 4096 + ((((i & 1) * 4 + 2 + (m >> 1)) ^ r8) << 4), c);
            mma16816(d0, a, bq[i][0], bq[i][1]);
            mma16816(d1, c, bq[i][2], bq[i][3]);
        }
    }
    r0 = (d0[0] + d0[1]) + (d1[0] + d1[1]);
    r1 = (d0[2] + d0[3]) + (d1[2] + d1[3]);
}

__device__ __forceinline__ void step32(uint32_t rows, uint32_t vecaddr, int lane, float (&d0)[4], float (&d1)[4]) {
    const int m = lane >> 3, r8 = lane & 7;
    const uint32_t a0 = rows + ((m >> 1) * 8 + r8) * 32 + (((m & 1) ^ (r8 >> 2)) << 4);
    uint4 t = lds4(vecaddr);
    uint32_t a[4], c[4];
    ldsm4t(a0, a);
    ldsm4t(a0 + 512, c);
    mma16816(d0, a, t.x, t.y);
    mma16816(d1, c, t.z, t.w);
}

__device__ __forceinline__ void reduce16_publish(uint32_t sb, float (&d0)[4], float (&d1)[4], int tid, int warp, int lane, unsigned char* dst, uint32_t tg) {
    if ((lane & 3) == 0) {
        sts1f(sb + S_R16 + (lane >> 2) * 32 + warp * 4, (d0[0] + d0[1]) + (d1[0] + d1[1]));
        sts1f(sb + S_R16 + ((lane >> 2) + 8) * 32 + warp * 4, (d0[2] + d0[3]) + (d1[2] + d1[3]));
    }
    bar_sync(2, 256);
    if (tid < 32) {
        float4 u = lds4f(sb + S_R16 + (tid & 15) * 32), v = lds4f(sb + S_R16 + (tid & 15) * 32 + 16);
        str1(dst + (tid & 15) * 4 + (tid >> 4) * 4096, tagf(((u.x + u.y) + (u.z + u.w)) + ((v.x + v.y) + (v.z + v.w)), tg));
    }
}

__device__ __forceinline__ uint32_t xo2(uint32_t a, uint32_t b, uint32_t t) {
    uint32_t r; asm("lop3.b32 %0, %1, %2, %3, 0x7E;" : "=r"(r) : "r"(a), "r"(b), "r"(t)); return r;
}
__device__ __forceinline__ uint32_t or3(uint32_t a, uint32_t b, uint32_t c) {
    uint32_t r; asm("lop3.b32 %0, %1, %2, %3, 0xFE;" : "=r"(r) : "r"(a), "r"(b), "r"(c)); return r;
}
__device__ __forceinline__ uint32_t bad2(const uint2& v, uint32_t tg) { return xo2(v.x, v.y, tg); }
__device__ __forceinline__ uint32_t bad4(const uint4& v, uint32_t tg) { return or3(xo2(v.x, v.y, tg), xo2(v.z, v.w, tg), 0); }
__device__ __forceinline__ bool nz4(const uint4& v) { return v.x != 0 && v.y != 0 && v.z != 0 && v.w != 0; }
__device__ __forceinline__ uint32_t clk32() { uint32_t c; asm volatile("mov.u32 %0, %%clock;" : "=r"(c)); return c; }
__device__ __forceinline__ void wait_until(uint32_t t0, uint32_t dt) {
#pragma unroll 1
    while ((int)(clk32() - t0 - dt) < 0) {}
}
__device__ __forceinline__ uint32_t mbar_mask4(uint32_t bar) {
    uint32_t m;
    asm volatile("{\n.reg .pred p, q, r, s;\n.reg .b32 a, b;\n"
                 "mbarrier.test_wait.parity.shared::cta.b64 p, [%1], 0;\n"
                 "mbarrier.test_wait.parity.shared::cta.b64 q, [%1+8], 0;\n"
                 "mbarrier.test_wait.parity.shared::cta.b64 r, [%1+16], 0;\n"
                 "mbarrier.test_wait.parity.shared::cta.b64 s, [%1+24], 0;\n"
                 "selp.u32 a, 1, 0, p;\nselp.u32 b, 2, 0, q;\nor.b32 a, a, b;\nselp.u32 b, 4, 0, r;\nor.b32 a, a, b;\n"
                 "selp.u32 b, 8, 0, s;\nor.b32 a, a, b;\nredux.sync.and.b32 %0, a, 0xffffffff;\n}" : "=r"(m) : "r"(bar) : "memory");
    return m;
}
__device__ __forceinline__ uint32_t probe_near(unsigned char* sp, uint32_t po, uint32_t sink) {
    uint32_t best0 = ~0u, best1 = ~0u;
#pragma unroll 1
    for (int r = 0; r < 5; r++) {
        uint32_t v; const uint32_t t0 = clk32();
        asm volatile("atom.relaxed.gpu.global.exch.b32 %0, [%1], %2;" : "=r"(v) : "l"(sp + po + (r & 1) * 4096), "r"(r) : "memory");
        sts1(sink, v);
        const uint32_t dt = clk32() - t0;
        if (r & 1) best1 = min(best1, dt); else best0 = min(best0, dt);
    }
    return (uint32_t)(best1 < best0) ^ (__popc(po & 0xB2000u) & 1u);
}
#define PIN(x) asm volatile("" : "+l"(x))
#define SPIN_CHECK(it) if (++(it) > SPIN_MAX) __trap()

__device__ __forceinline__ void mod2_tile(uint32_t sb, unsigned char* sp, uint32_t bars, int b, int nt, int lane, uint32_t tg) {
    const int m = lane >> 3, r8 = lane & 7, q = lane & 3;
    const uint32_t a0 = sb + S_MOD2 + ((m >> 1) * 8 + r8) * 64 + (((nt * 2 + (m & 1)) ^ (r8 >> 1)) << 4);
    const uint32_t v0 = sb + S_SC + (b >> 6) * 1024 + ((lane >> 2) & 1) * 64 + q * 16;
    float d0[4] = {0.f, 0.f, 0.f, 0.f}, d1[4] = {0.f, 0.f, 0.f, 0.f};
#pragma unroll 1
    for (int c = 0; c < 2; c++) {
        mbar_wait(bars + (C_MOD2 + c) * 8);
#pragma unroll
        for (int i = 0; i < 4; i++) {
            const uint4 t = lds4(v0 + (c * 4 + i) * 128);
            uint32_t a[4], e[4];
            ldsm4t(a0 + c * 8192 + i * 2048, a); ldsm4t(a0 + c * 8192 + i * 2048 + 1024, e);
            mma16816(d0, a, t.x, t.y); mma16816(d1, e, t.z, t.w);
        }
    }
    const float r0 = (d0[0] + d0[1]) + (d1[0] + d1[1]), r1 = (d0[2] + d0[3]) + (d1[2] + d1[3]);
    const float t0 = __shfl_sync(~0u, r0, lane & 28), t1 = __shfl_sync(~0u, r1, lane & 28);
    str1(sp + G_MOD2 + spread(b * 128 + nt * 64 + (q & 1) * 32 + (lane >> 2) * 4) + (q >> 1) * 4096, tagf((q & 1) ? t1 : t0, tg));
}

__global__ void __cluster_dims__(2, 1, 1) __launch_bounds__(NTHR, 1) fused_decode_kernel(const __grid_constant__ Params p) {
    extern __shared__ __align__(1024) unsigned char smem_raw[];
    const uint32_t sb = (uint32_t)__cvta_generic_to_shared(smem_raw);
    const int tid = threadIdx.x, lane = tid & 31;
    const int warp = __shfl_sync(~0u, tid >> 5, 0);
    const int b = blockIdx.x, h = b >> 2, j = b & 3, rank = b & 1, pair = b >> 1;
    const uint32_t bars = sb + S_BAR;
    unsigned char* const sp = p.s;
    const uint32_t t_start = clk32();

    if (warp == 11) {
        float d[4] = {0.f, 0.f, 0.f, 0.f};
        const uint32_t zz = t_start & 0x00010001u, z[4] = {zz, zz, zz, zz};
        mma16816(d, z, zz, zz);
        bar_sync(1, NTHR - 64);
        uint32_t done = 0;
#pragma unroll 1
        for (int i = 0; i < 4096 && done < 2; i++) {
            mma16816(d, z, zz, zz);
            __nanosleep(200);
            done += mbar_mask4(bars + B_F * 8) & 1;
        }
        if (d[0] == 1.f) sts1f(sb + S_EP + 12, d[1]);
        return;
    }
    if (warp == 8) {
        TS(30);
        if (lane == 0) {
            mbar_init(bars, 1);
            asm volatile("fence.mbarrier_init.release.cluster;" ::: "memory");
            mbar_expect_tx(bars, 8192);
            tma4(sb + S_MOD1, &p.m[0], (b >> 1) * 16, (b & 1) * 256, 0, 0, bars, POL_FIRST);
            TS(28);
#pragma unroll
            for (int i = 1; i < NBAR; i++) mbar_init(bars + i * 8, i == B_UK ? 8 : i == B_O ? 4 : 1);
            asm volatile("fence.mbarrier_init.release.cluster;" ::: "memory");
            mbar_expect_tx(bars + B_X * 8, 8192); mbar_expect_tx(bars + (B_X + 1) * 8, 8192);
        }
        __syncwarp();
        TS(27);
        bar_arrive(1, NTHR - 64);
        {
            const int c = lane + 1;
            int mi = 1, k = c - C_WQ, c0 = 0, c1 = j * 128, d1 = 32, c2 = h * 2, c3 = 0, dst = S_WQ;
            if (c >= C_WUK)  { mi = 2; k = c - C_WUK; dst = S_WUK; }
            if (c >= C_CKV)  { mi = 3; k = c - C_CKV; dst = S_CKV; c1 = pair * 128 + (k >> 2) * 64; d1 = 0; c2 = rank * 4 + (k & 3); }
            if (c >= C_T1)   { const int x = (c - C_T1) & 1; k = (c - C_T1) >> 1; dst = x ? S_XCH : S_CKV + 6 * 8192; c1 = pair * 128 + 64; c2 = (rank ^ x) * 4 + 2 + k; }
            if (c >= C_WUV)  { mi = 4; k = c - C_WUV; dst = S_WUV; c1 = j * 16; c2 = k * 2; c3 = h * 2; }
            if (c >= C_WUV + 4) { mi = 5; k = c - C_WO; dst = S_WO; c0 = (b & 15) * 32; c1 = (b >> 4) * 512; d1 = 128; c2 = 0; c3 = 0; }
            if (c == C_MOD2 || c == C_MOD2 + 1) { mi = 8; k = c - C_MOD2; dst = S_MOD2; c0 = 1024 + (b & 63) * 32; c1 = (b >> 6) * 256; }
            if (c >= C_W1)   { mi = 6; k = c - C_W1; dst = S_W1; c0 = b * 16; c1 = 0; d1 = 256; }
            if (c >= C_W2)   { mi = 7; k = c - C_W2; dst = S_W2; c0 = 0; c1 = b * 32; d1 = 16; }
            const uint32_t wa = (uint32_t)c0 | (uint32_t)(c1 + k * d1) << 16;
            const bool keep = c >= C_T1 && c < C_WUV;
            const uint32_t wb = (uint32_t)c2 | (uint32_t)c3 << 8 | (uint32_t)mi << 14 | (uint32_t)keep << 18 | (uint32_t)((dst >> 13) + k) << 24;
            const int nch = b < NFFN ? NCHUNK : C_W1;
#pragma unroll 1
            for (int i = 1; i < nch; i++) {
                const uint32_t ua = __shfl_sync(~0u, wa, i - 1), ub = __shfl_sync(~0u, wb, i - 1);
                if (i == C_T1 + 1) mbar_wait(bars + B_UK * 8);
                if (i == C_W1) mbar_wait(bars + B_QK * 8);
                if (i >= WIN) mbar_wait(bars + (i - WIN) * 8);
                wait_until(t_start, p.sched[i]);
                if (lane == 0) {
                    mbar_expect_tx(bars + i * 8, 8192);
                    tma4(sb + (ub >> 24) * 8192, &p.m[(ub >> 14) & 15], ua & 0xffff, ua >> 16, ub & 0xff, (ub >> 8) & 0x3f, bars + i * 8,
                         (ub >> 18 & 1) ? POL_NORMAL : POL_FIRST);
                }
            }
        }
        TS(20);
        return;
    }
    if (warp == 9) {
        const int col = (lane & 1) * 4 + (lane & 2) + ((lane >> 2) & 1);
        const float be = __bfloat162float(p.b2[(b & 63) * 8 + col]);
        const uint32_t pr0 = G_PROBE + b * 32;
        if (lane < 4) str4(sp + pr0 + (lane & 2) * 2048 + (lane & 1) * 16, 0, 0, 0, 0);
        __syncwarp();
        uint32_t beta = 0;
        if (lane == 0) { beta = probe_near(sp, pr0, sb + S_EP + 12); sts1(sb + S_EP + 4, beta); }
        __syncwarp();
        bar_sync(8, 64);
        if (lane == 0) mbar_arrive(bars + B_BETA * 8);
        TS(69);
        const uint32_t ep = lds1(sb + S_EP);
        const uint32_t tg = ~ep & 1u;
        beta = __shfl_sync(~0u, beta, 0);
        const unsigned char* sg = sp + pick(G_MOD2 + spread((lane & 8) * 1024 + 6144 + (b & 63) * 32 + col * 4), beta);
        const unsigned char* s7 = sp + pick(G_H7 + (b & 63) * 8192 + lane * 16, beta);
        const unsigned char* s7c = s7 + (lane < 2 * (NFFN - 80) ? 2560 : 0);
        mod2_tile(sb, sp, bars, b, 0, lane, tg);
        TS(29);
        if (b >= 64) return;
        mbar_wait(bars + B_F * 8);
        uint32_t w; int it = 0;
#pragma unroll 1
        do { w = ldr1(sg); SPIN_CHECK(it); } while (__any_sync(~0u, (w ^ tg) & 1));
        const float gb = u2f(w) + __shfl_xor_sync(~0u, u2f(w), 8);
        bar_sync(10, 320);
        const uint32_t t_6 = clk32();
        const float x2 = fmaf(gb, be, lds1f(sb + S_X2 + col * 4));
        TS(21);
        wait_until(t_6, p.tm[D_H7]);
        uint4 y[6];
#pragma unroll 1
        do {
#pragma unroll
            for (int i = 0; i < 5; i++) y[i] = ldr4(s7 + i * 512);
            y[5] = ldr4(s7c);
            SPIN_CHECK(it);
        } while (__any_sync(~0u, or3(or3(bad4(y[0], tg), bad4(y[1], tg), bad4(y[2], tg)), or3(bad4(y[3], tg), bad4(y[4], tg), bad4(y[5], tg)), 0) & 1));
        if (lane >= 2 * (NFFN - 80)) y[5] = make_uint4(0, 0, 0, 0);
        const float s0 = ((u2f(y[0].x) + u2f(y[1].x)) + (u2f(y[2].x) + u2f(y[3].x))) + (u2f(y[4].x) + u2f(y[5].x));
        const float s1 = ((u2f(y[0].y) + u2f(y[1].y)) + (u2f(y[2].y) + u2f(y[3].y))) + (u2f(y[4].y) + u2f(y[5].y));
        const float s2 = ((u2f(y[0].z) + u2f(y[1].z)) + (u2f(y[2].z) + u2f(y[3].z))) + (u2f(y[4].z) + u2f(y[5].z));
        const float s3 = ((u2f(y[0].w) + u2f(y[1].w)) + (u2f(y[2].w) + u2f(y[3].w))) + (u2f(y[4].w) + u2f(y[5].w));
        {
            const bool b1 = lane & 2, b2 = lane & 4;
            const float k0 = (b1 ? s2 : s0) + __shfl_xor_sync(~0u, b1 ? s0 : s2, 2), k1 = (b1 ? s3 : s1) + __shfl_xor_sync(~0u, b1 ? s1 : s3, 2);
            float k = (b2 ? k1 : k0) + __shfl_xor_sync(~0u, b2 ? k0 : k1, 4);
            k += __shfl_xor_sync(~0u, k, 8); k += __shfl_xor_sync(~0u, k, 16);
            if (lane < 8) p.out[b * 8 + col] = __float2bfloat16(fmaf(gb, k, x2));
            if (b == 0 && lane == 8) str1(sp + G_EPOCH, ep + 1);
        }
        TS(22);
        return;
    }

    if (warp == 10) {
        const float b1v = __bfloat162float(p.b1[(b < NFFN ? b * 16 : 0) + (lane & 15)]);
        const uint32_t pr4 = G_H4 + pair * 131072 + 65536 + rank * 256;
        const uint32_t prev = ldr1(sp + pr4 + 128);
        if (lane < 4) str4(sp + pr4 + (lane & 2) * 2048 + (lane & 1) * 16, 0, 0, 0, 0);
        __syncwarp();
        uint32_t beta4 = 0;
        if (lane == 0) beta4 = probe_near(sp, pr4, sb + S_X2);
        beta4 = __shfl_sync(~0u, beta4, 0);
        bar_sync(11, 64);
        const uint32_t tg = ~lds1(sb + S_EP) & 1u;
        {
            const uint32_t held = (prev & 24) ^ (8u << beta4), t4 = held >> (3 + beta4) & 1;
            const uint32_t w = tg | beta4 << 1 | t4 << 2 | held;
            if (lane < 2) str4(sp + pr4 + 128 + lane * 16, w, w, w, w);
            if (lane == 0) sts1(sb + S_EP + 8, w);
#pragma unroll 1
            for (int i = 0; i < 32; i++) {
                wait_until(t_start, WARM_T0 + i * WARM);
                str4(sp + pick(G_H4 + pair * 131072 + spread((i * 4 + (lane >> 3)) * 256 + rank * 128 + (lane & 7) * 16), beta4), t4 ^ 1, 0, t4 ^ 1, 0);
            }
            __syncwarp();
            if (lane == 0) mbar_arrive(bars + B_BETA4 * 8);
        }
        TS(70);
        mbar_wait(bars + B_BETA * 8);
        const uint32_t beta = lds1(sb + S_EP + 4);
        const unsigned char* sm_a = sp + pick(G_ML + spread(lane * 256 + h * 4), beta);
        const unsigned char* sm_b = sp + pick(G_ML + spread((lane + 32) * 256 + h * 4), beta);
        mbar_wait(bars + B_QK * 8);
        wait_until(clk32(), p.tm[D_H4]);
        wait_until(t_start, p.tm[T_H4] - p.tm[A_H4] / 2);
        uint32_t ma, mb, la, lb; int it = 0;
        TS(76);
#pragma unroll 1
        do {
            ma = ldr1(sm_a); mb = ldr1(sm_b); la = ldr1(sm_a + 128); lb = ldr1(sm_b + 128);
            SPIN_CHECK(it);
        } while (__any_sync(~0u, (xo2(ma, mb, tg) | xo2(la, lb, tg)) & 1));
        TS(77);
        float M = fmaxf(u2f(ma), u2f(mb));
#pragma unroll
        for (int o = 16; o; o >>= 1) M = fmaxf(M, __shfl_xor_sync(~0u, M, o));
        const float wa = ex2(u2f(ma) - M), wb = ex2(u2f(mb) - M);
        float L = wa * u2f(la) + wb * u2f(lb);
#pragma unroll
        for (int o = 16; o; o >>= 1) L += __shfl_xor_sync(~0u, L, o);
        L = __fdividef(1.f, L);
        sts1f(sb + S_ML + lane * 4, wa * L); sts1f(sb + S_ML + 128 + lane * 4, wb * L);
        __syncwarp();
        if (lane == 0) mbar_arrive(bars + B_W * 8);
        TS(78);
        mod2_tile(sb, sp, bars, b, 1, lane, tg);
        if (b < NFFN) {
            const uint32_t a = sb + S_RED + (lane & 15) * 32 + (lane >> 4) * 16;
            const uint32_t as = sb + S_RED + 1536 + (lane >> 4) * 16;
            bar_sync(9, 288);
            const float4 sa = lds4f(as + 8 * 32), ta = lds4f(as + 6 * 32), tc = lds4f(as + 7 * 32);
            const float4 U = lds4f(a), G = lds4f(a + 512), S = lds4f(a + 1024);
            float mu = (sa.x + sa.y) + (sa.z + sa.w), ex = ((ta.x + ta.y) + (ta.z + ta.w)) + ((tc.x + tc.y) + (tc.z + tc.w));
            float us = (U.x + U.y) + (U.z + U.w), gs = (G.x + G.y) + (G.z + G.w), ss = (S.x + S.y) + (S.z + S.w);
            mu += __shfl_xor_sync(~0u, mu, 16); ex += __shfl_xor_sync(~0u, ex, 16);
            us += __shfl_xor_sync(~0u, us, 16); gs += __shfl_xor_sync(~0u, gs, 16); ss += __shfl_xor_sync(~0u, ss, 16);
            mu *= 1.f / 512.f;
            float rstd;
            asm("rsqrt.approx.ftz.f32 %0, %1;" : "=f"(rstd) : "f"(fmaxf(fmaf(ex, 1.f / 512.f, -mu * mu), 0.f) + 1e-5f));
            const float pre = (us - mu * gs) * rstd + (ss + b1v);
            const float z = pre * fmaf(pre * pre, 0.044715f * 2.302208198f, 2.302208198f);
            sts1f(sb + S_STAT + (lane & 15) * 4, __fdividef(pre, 1.f + ex2(fminf(-z, 126.f))));
            bar_arrive(10, b < 64 ? 320 : 288);
        }
        return;
    }

    const int g = lane >> 2, q = lane & 3;
    const int wg = warp >> 2, wq = warp & 3;
    const uint32_t ep0 = ldr1(sp + G_EPOCH);
    const uint32_t tg = ~ep0 & 1u;
    const uint32_t cw = *reinterpret_cast<const uint32_t*>(p.c + tid * 2);
    const uint4 xa = *reinterpret_cast<const uint4*>(p.x + lane * 16), xb = *reinterpret_cast<const uint4*>(p.x + lane * 16 + 8);
    const uint32_t xw2 = *reinterpret_cast<const uint32_t*>(p.x + tid * 2);
    const float xm = __bfloat162float(p.x[j * 128 + (tid & 127)]);
    {
        uint32_t z = ~0u, zv = tg ^ 1u;
        if (tid < 4) z = G_H1 + spread((b & 1) * 4096 + (b >> 1) * 64 + tid * 16);
        else if (tid >= 8 && tid < 16) z = G_MOD2 + spread(b * 128 + (tid & 7) * 16);
        else if (tid >= 112 && tid < 120) z = G_H6 + spread(b * 128 + (tid & 7) * 16);
        else if (tid >= 16 && tid < 32) { const uint32_t o = G_ML + spread(pair * 256 + (tid & 15) * 16) + rank * 4096; str4(sp + o, zv, zv, zv, zv); }
        else if (tid >= 32 && tid < 64) z = G_H2 + spread(b * 512 + lane * 16);
        else if (tid >= 64 && tid < 96) z = G_H5 + spread(b * 512 + lane * 16);
        else if (tid >= 96 && tid < 112) { z = G_H3 + spread((j * 2 + ((tid >> 3) & 1)) * 4096 + h * 128 + (tid & 7) * 16); zv = 0; }
        if (z != ~0u) { str4(sp + z, zv, zv, zv, zv); str4(sp + z + 4096, zv, zv, zv, zv); }
    }
    if (tid == 0) sts1(sb + S_EP, ep0);
    if (tid < 64) sts1(sb + S_MAX + tid * 4, 0x80000000u);
    sts1(sb + S_ONES + tid * 4, 0x3F803F80u);
    {
        const float c0 = bflo(cw), c1 = bfhi(cw);
        const float s0 = __fdividef(c0, 1.f + __expf(fminf(-c0, 80.f))), s1 = __fdividef(c1, 1.f + __expf(fminf(-c1, 80.f)));
        uint32_t hi, lo; split2(s0, s1, hi, lo);
        const uint32_t a = sb + S_SC + (tid >> 4) * 128 + vpos((tid & 15) * 2);
        sts1(a, hi); sts1(a + 64, lo);
    }
    TS0(0);
    bar_sync(1, NTHR - 64);
    if (warp == 7) bar_arrive(8, 64); else if (warp == 6) bar_arrive(11, 64);

    const uint32_t vlane = (g & 1) * 64 + q * 16;

    {
        float d0[4] = {0.f, 0.f, 0.f, 0.f}, d1[4] = {0.f, 0.f, 0.f, 0.f};
        mbar_wait(bars + C_MOD1 * 8);
        step32(sb + S_MOD1 + warp * 1024, sb + S_SC + ((b & 1) * 8 + warp) * 128 + vlane, lane, d0, d1);
        reduce16_publish(sb, d0, d1, tid, warp, lane, sp + G_H1 + spread((b & 1) * 4096 + (b >> 1) * 64), tg);
    }
    TS0(1);
    float mean1, rstd1;
    {
        const uint32_t w[8] = {xa.x, xa.y, xa.z, xa.w, xb.x, xb.y, xb.z, xb.w};
        float s = 0.f;
#pragma unroll
        for (int i = 0; i < 8; i++) s += bflo(w[i]) + bfhi(w[i]);
#pragma unroll
        for (int o = 16; o; o >>= 1) s += __shfl_xor_sync(~0u, s, o);
        mean1 = s * (1.f / 512.f);
        float v = 0.f;
#pragma unroll
        for (int i = 0; i < 8; i++) { float a = bflo(w[i]) - mean1, c = bfhi(w[i]) - mean1; v += a * a + c * c; }
#pragma unroll
        for (int o = 16; o; o >>= 1) v += __shfl_xor_sync(~0u, v, o);
        rstd1 = rsqrtf(v * (1.f / 512.f) + 1e-5f);
    }
    if (tid < 128) {
        const unsigned char* s0 = sp + G_H1 + j * 512 + tid * 4;
        const unsigned char* s1 = s0 + 8192;
        uint4 a; int it = 0;
        wait_until(t_start, p.tm[T_H1]);
#pragma unroll 1
        do {
            a.x = ldr1(s0); a.y = ldr1(s1); a.z = ldr1(s0 + 2048); a.w = ldr1(s1 + 2048);
            SPIN_CHECK(it);
        } while (bad4(a, tg) & 1);
        const float hv = (xm - mean1) * rstd1 * (1.f + (u2f(a.z) + u2f(a.w))) + (u2f(a.x) + u2f(a.y));
        uint32_t hi, lo; split2(hv, 0.f, hi, lo);
        const uint32_t ad = sb + S_VEC + (tid >> 5) * 128 + vpos(tid & 31);
        stsh(ad, hi); stsh(ad + 64, lo);
    }
    TS0(2);
    bar_sync(2, 256);
    {
        float r0, r1;
        gemv128<true>(sb + S_WQ, sb + S_VEC, bars + C_WQ * 8, warp, lane, r0, r1);
        const float t0 = __shfl_sync(~0u, r0, lane & 28), t1 = __shfl_sync(~0u, r1, lane & 28);
        str1(sp + G_H2 + spread(b * 512 + warp * 64 + (q & 1) * 32 + g * 4) + (q >> 1) * 4096, tagf((q & 1) ? t1 : t0, tg));
    }
    TS0(3);
    mbar_wait(bars + B_BETA * 8);
    const uint32_t beta = lds1(sb + S_EP + 4);
    bar_sync(2, 256);
    if (tid < 128) {
        const unsigned char* src = sp + pick(G_H2 + spread(h * 2048 + tid * 4), beta);
        uint4 a; int it = 0;
#pragma unroll 1
        do {
            a.x = ldr1(src); a.y = ldr1(src + 512); a.z = ldr1(src + 1024); a.w = ldr1(src + 1536);
            SPIN_CHECK(it);
        } while (bad4(a, tg) & 1);
        const float qv = ((u2f(a.x) + u2f(a.y)) + (u2f(a.z) + u2f(a.w))) * (0.08838834764831845f * 1.4426950408889634f);
        uint32_t hi, lo; split2(qv, 0.f, hi, lo);
        const uint32_t ad = sb + S_VEC + (tid >> 5) * 128 + vpos(tid & 31);
        stsh(ad, hi); stsh(ad + 64, lo);
    }
    TS0(4);
    bar_sync(2, 256);
    {
        float r0, r1;
        gemv128<false>(sb + S_WUK, sb + S_VEC, bars + C_WUK * 8, warp, lane, r0, r1);
        const float n0 = __shfl_down_sync(~0u, r0, 4), m0 = __shfl_up_sync(~0u, r1, 4);
        const uint32_t w = (g & 1) ? packbf(m0, r1) : packbf(r0, n0);
        const uint32_t w2 = __shfl_sync(~0u, w, lane & 28);
        if (q < 2) {
            const int chunk = ((warp & 3) * 2 + (g & 1)) ^ (h & 7);
            str1(sp + G_H3 + (j * 2 + (warp >> 2)) * 8192 + q * 4096 + h * 128 + chunk * 16 + (g >> 1) * 4, w2 ^ 0xFFFF0000u);
        }
        if (lane == 0) mbar_arrive(bars + B_UK * 8);
    }
    TS0(5);
    {
        const unsigned char* src[6];
#pragma unroll
        for (int i = 0; i < 6; i++) src[i] = sp + pick(G_H3 + (i < 4 ? rank * 4 + i : (rank ^ 1) * 4 + i - 2) * 8192 + tid * 16, beta);
        uint4 v[6];
        wait_until(t_start, p.tm[T_H3]);
#pragma unroll
        for (int i = 0; i < 6; i++) v[i] = ldr4(src[i]);
        int it = 0;
#pragma unroll 1
        while (true) {
            bool ok = true;
#pragma unroll
            for (int i = 0; i < 6; i++) if (!nz4(v[i])) { v[i] = ldr4(src[i]); ok = false; }
            if (__all_sync(~0u, ok)) break;
            SPIN_CHECK(it);
        }
        TS0(31);
#pragma unroll
        for (int i = 0; i < 6; i++)
            sts4(sb + S_QABS + i * 4096 + tid * 16, v[i].x ^ 0xFFFF0000u, v[i].y ^ 0xFFFF0000u, v[i].z ^ 0xFFFF0000u, v[i].w ^ 0xFFFF0000u);
        fence_async();
        bar_sync(2, 256);
    }
    TS0(6);
    if (wg) {
        uint32_t bw; int it = 0;
#pragma unroll 1
        do { bw = ldr1(sp + G_H4 + 65536 + 128 + ((tid & 127) >> 1) * 131072 + (tid & 1) * 256); SPIN_CHECK(it); } while (__any_sync(~0u, (bw ^ tg) & 1));
        const uint32_t mb = __ballot_sync(~0u, bw & 2), mt = __ballot_sync(~0u, bw & 4);
        if (lane == 0) sts2(sb + S_B4 + wq * 8, mb, mt);
    }
    if (b < NFFN) {
        unsigned char* d7 = sp + G_H7 + (tid >> 2) * 8192 + b * 32 + (tid & 3) * 8;
        str2(d7, tg ^ 1, tg ^ 1); str2(d7 + 4096, tg ^ 1, tg ^ 1);
    }
    {
        float s[16];
#pragma unroll
        for (int i = 0; i < 16; i++) s[i] = 0.f;
        const uint32_t xo = (wg ? S_XBUF1 : S_XBUF0) + (tid & 127) * 16;
#pragma unroll 1
        for (int cg = 0; cg < 4 - 2 * wg; cg++) {
            mbar_wait(bars + (C_CKV + wg * 4 + cg) * 8);
            const uint64_t da = mkdesc(sb + S_CKV + (wg * 4 + cg) * 8192), db = mkdesc(sb + S_QABS + cg * 4096);
            wg_fence();
#pragma unroll
            for (int k = 0; k < 4; k++) wgmma_n32<0>(s, da + k * 2, db + k * 2, 1);
            wg_commit();
        }
        wg_wait<0>();
        reg_fence16(s);
        TS0(64);
        {
            uint32_t ra, rb;
            asm("mapa.shared::cluster.u32 %0, %1, %2;" : "=r"(ra) : "r"(sb + xo), "r"(rank ^ 1));
            asm("mapa.shared::cluster.u32 %0, %1, %2;" : "=r"(rb) : "r"(bars + (B_X + wg) * 8), "r"(rank ^ 1));
#pragma unroll
            for (int i = 0; i < 4; i++)
                asm volatile("st.async.weak.shared::cluster.mbarrier::complete_tx::bytes.v4.f32 [%0], {%1,%2,%3,%4}, [%5];"
                             ::"r"(ra + i * 2048), "f"(s[4 * i]), "f"(s[4 * i + 1]), "f"(s[4 * i + 2]), "f"(s[4 * i + 3]), "r"(rb) : "memory");
        }
        float4 xs[4];
#define QK_TAIL(c) do { \
            mbar_wait2(bars + (C_T1 + 2 * (c)) * 8); \
            const uint64_t da = mkdesc(sb + S_CKV + (6 + (c)) * 8192), dx = mkdesc(sb + S_XCH + (c) * 8192), db = mkdesc(sb + S_QABS + (2 + (c)) * 4096); \
            wg_fence(); \
            _Pragma("unroll") for (int k = 0; k < 4; k++) { wgmma_n32<0>(s, da + k * 2, db + k * 2, 1); wgmma_n32<0>(s, dx + k * 2, db + 512 + k * 2, 1); } \
            wg_commit(); } while (0)
        if (wg) QK_TAIL(0);
        mbar_wait_cluster(bars + (B_X + wg) * 8);
#pragma unroll
        for (int i = 0; i < 4; i++) xs[i] = lds4f(sb + xo + i * 2048);
        if (wg) QK_TAIL(1);
        wg_wait<0>();
        reg_fence16(s);
        TS4(7); TS0(65);
#pragma unroll
        for (int i = 0; i < 4; i++) { s[4 * i] += xs[i].x; s[4 * i + 1] += xs[i].y; s[4 * i + 2] += xs[i].z; s[4 * i + 3] += xs[i].w; }
        const bool b2 = lane & 16, b1 = lane & 8, b0 = lane & 4;
        {
            float v[8];
#pragma unroll
            for (int i = 0; i < 4; i++) { v[2 * i] = fmaxf(s[4 * i], s[4 * i + 2]); v[2 * i + 1] = fmaxf(s[4 * i + 1], s[4 * i + 3]); }
            float u[4];
#pragma unroll
            for (int k = 0; k < 4; k++) u[k] = fmaxf(b2 ? v[k + 4] : v[k], __shfl_xor_sync(~0u, b2 ? v[k] : v[k + 4], 16));
            float t[2];
#pragma unroll
            for (int k = 0; k < 2; k++) t[k] = fmaxf(b1 ? u[k + 2] : u[k], __shfl_xor_sync(~0u, b1 ? u[k] : u[k + 2], 8));
            const uint32_t r = ordf(__float_as_uint(fmaxf(b0 ? t[1] : t[0], __shfl_xor_sync(~0u, b0 ? t[0] : t[1], 4))));
            const uint32_t a = sb + S_MAX + (8 * (g >> 1) + 2 * q + (g & 1)) * 4;
            red_max(a + 128, r);
            if (wg == 0) red_max(a, r);
        }
        if (wg == 0) { bar_arrive(4, 256); bar_sync(3, 128); } else { bar_arrive(7, 256); bar_sync(4, 256); }
        TS4(66);
        uint32_t pk[8];
#pragma unroll
        for (int i = 0; i < 4; i++) {
            const float2 mm = lds2f(sb + S_MAX + wg * 128 + (8 * i + 2 * q) * 4);
            const float m0 = u2f(ordf(__float_as_uint(mm.x))), m1 = u2f(ordf(__float_as_uint(mm.y)));
            pk[2 * i] = packbf(ex2(s[4 * i] - m0), ex2(s[4 * i + 1] - m1));
            pk[2 * i + 1] = packbf(ex2(s[4 * i + 2] - m0), ex2(s[4 * i + 3] - m1));
        }
        {
            const int t = lane >> 3, r8 = lane & 7;
            const uint32_t a = sb + S_P + wg * 4096 + ((t >> 1) * 8 + r8) * 128 + (((2 * wq + (t & 1)) ^ r8) << 4);
            stsm4t(a, pk[0], pk[1], pk[2], pk[3]);
            stsm4t(a + 2048, pk[4], pk[5], pk[6], pk[7]);
        }
        fence_async();
        TS4(67); TS0(68);
        if (wg) {
            bar_arrive(5, 256);
            if (warp == 4) {
                str1(sp + G_ML + spread(pair * 256 + lane * 4) + rank * 4096, tagf(u2f(ordf(lds1(sb + S_MAX + 128 + lane * 4))), tg));
                if (lane == 0) mbar_arrive(bars + B_QK * 8);
            }
        } else {
            float o0[16], o1[16], o2[16], o3[16], ol[16];
            const uint64_t d1 = mkdesc(sb + S_ONES) & ~(0x3FFFull << 32);
            const uint64_t db = mkdesc(sb + S_P), da = mkdesc(sb + S_CKV);
            bar_sync(3, 128);
            wg_fence();
#pragma unroll
            for (int k = 0; k < 4; k++) {
                wgmma_n32<1>(o0, da + k * 128, db + k * 2, k);
                wgmma_n32<1>(o1, da + 512 + k * 128, db + k * 2, k);
                wgmma_n32<1>(o2, da + 1024 + k * 128, db + k * 2, k);
                wgmma_n32<1>(o3, da + 1536 + k * 128, db + k * 2, k);
                wgmma_n32<0>(ol, d1, db + k * 2, k);
            }
            wg_commit();
            wg_wait<0>();
            reg_fence16(o0); reg_fence16(o1); reg_fence16(o2); reg_fence16(o3); reg_fence16(ol);
            TS0(23);
            bar_sync(7, 256);
            {
                const float al = ex2(u2f(ordf(lds1(sb + S_MAX + lane * 4))) - u2f(ordf(lds1(sb + S_MAX + 128 + lane * 4))));
#pragma unroll
                for (int i = 0; i < 4; i++) {
                    const float a0 = __shfl_sync(~0u, al, 8 * i + 2 * q), a1 = __shfl_sync(~0u, al, 8 * i + 2 * q + 1);
                    o0[4 * i] *= a0; o0[4 * i + 1] *= a1; o0[4 * i + 2] *= a0; o0[4 * i + 3] *= a1;
                    o1[4 * i] *= a0; o1[4 * i + 1] *= a1; o1[4 * i + 2] *= a0; o1[4 * i + 3] *= a1;
                    o2[4 * i] *= a0; o2[4 * i + 1] *= a1; o2[4 * i + 2] *= a0; o2[4 * i + 3] *= a1;
                    o3[4 * i] *= a0; o3[4 * i + 1] *= a1; o3[4 * i + 2] *= a0; o3[4 * i + 3] *= a1;
                    ol[4 * i] *= a0; ol[4 * i + 1] *= a1; ol[4 * i + 2] *= a0; ol[4 * i + 3] *= a1;
                }
            }
            mbar_wait(bars + B_BETA4 * 8);
            const uint32_t rec = lds1(sb + S_EP + 8), tg4w = rec >> 2 & 1;
            unsigned char* const h4dst = sp + pick(G_H4 + pair * 131072 + spread(q * 2048 + wq * 256 + rank * 128 + g * 8), rec >> 1);
            unsigned char* ldst = sp + G_ML + spread(pair * 256 + 128 + wq * 32 + q * 8) + rank * 4096;
            PIN(ldst);
            TS0(81);
            bar_sync(5, 256);
            wg_fence();
#pragma unroll
            for (int k = 0; k < 4; k++) {
                wgmma_n32<1>(o0, da + 2048 + k * 128, db + 256 + k * 2, 1);
                wgmma_n32<1>(o1, da + 2048 + 512 + k * 128, db + 256 + k * 2, 1);
            }
            wg_commit();
            wg_wait<0>();
            reg_fence16(o0); reg_fence16(o1);
            TS0(24);
            wg_fence();
#pragma unroll
            for (int k = 0; k < 4; k++) wgmma_n32<1>(o2, da + 2048 + 1024 + k * 128, db + 256 + k * 2, 1);
            wg_commit();
#define O_STORE(A, B, OFF) _Pragma("unroll") for (int i = 0; i < 4; i++) _Pragma("unroll") for (int e = 0; e < 2; e++) { \
                const float f0 = u2f((__float_as_uint(A[4 * i + e]) + 0x10000u) & 0xFFFE0000u); \
                str64(h4dst + (OFF) + i * 16384 + e * 1024, packbf(f0, A[4 * i + 2 + e]) | tg4w, packbf(B[4 * i + e], B[4 * i + 2 + e])); }
            TS0(8);
            O_STORE(o0, o1, 0);
            __syncwarp();
            wg_fence();
#pragma unroll
            for (int k = 0; k < 4; k++) {
                wgmma_n32<1>(o3, da + 2048 + 1536 + k * 128, db + 256 + k * 2, 1);
                wgmma_n32<0>(ol, d1, db + 256 + k * 2, 1);
            }
            wg_commit();
            wg_wait<0>();
            reg_fence16(o2); reg_fence16(o3); reg_fence16(ol);
            {
                const float l0 = (wq & 2) ? ((wq & 1) ? ol[12] : ol[8]) : ((wq & 1) ? ol[4] : ol[0]);
                const float l1 = (wq & 2) ? ((wq & 1) ? ol[13] : ol[9]) : ((wq & 1) ? ol[5] : ol[1]);
                if (g == 0) str2(ldst, tagf(l0, tg), tagf(l1, tg));
            }
            O_STORE(o2, o3, 64);
            if (lane == 0) mbar_arrive(bars + B_O * 8);
        }
    }
    TS0(9);
    const uint32_t t_o = clk32();
    uint32_t af[8][4];
    {
        const int sg = wq * 4 + (lane >> 3), ur = (lane >> 2) & 1;
        const int po = ur * 128 + (wg ^ 1) * 64 + q * 16;
        uint32_t a0;
        {
            const int m = lane >> 3, r8 = lane & 7;
            const int row = (m >> 1) * 16 + (r8 >> 1) * 2 + (r8 & 1) * 8;
            a0 = sb + S_WUV + wg * 4096 + row * 128 + (((wq * 2 + (m & 1)) ^ (row & 7)) << 4);
        }
        const unsigned char* src[4];
        uint32_t tg4[4];
#pragma unroll
        for (int i = 0; i < 4; i++) {
            const float2 m = lds2f(sb + S_B4 + i * 8);
            src[i] = sp + pick(G_H4 + (sg + 16 * i) * 131072 + spread(b * 256 + po), __float_as_uint(m.x) >> (sg * 2 + ur));
            tg4[i] = __float_as_uint(m.y) >> (sg * 2 + ur);
        }
        uint4 v[4];
        uint32_t have = 0;
        int it = 0;
        unsigned char* d5 = sp + G_H5 + spread(b * 512 + warp * 64 + (q & 1) * 32 + g * 4) + (q >> 1) * 4096;
        PIN(d5);
        if (wg) mbar_wait(bars + B_O * 8);
        wait_until(wg ? clk32() - p.tm[A_H4] : t_o, p.tm[D_H4]);
        wait_until(t_start, p.tm[T_H4] - (wg ? p.tm[A_H4] : 0));
#pragma unroll
        for (int i = 0; i < 4; i++) v[i] = ldr64x2(src[i]);
        TS0(10);
#define LOAD_UV(now) _Pragma("unroll") for (int i = 0; i < 4; i++) \
            if ((now) >> i & 1) { ldsm4t(a0 + i * 8192, af[2 * i]); ldsm4t((a0 + i * 8192 + 128) ^ 16, af[2 * i + 1]); }
        have = mbar_mask4(bars + C_WUV * 8);
        LOAD_UV(have);
        mbar_wait(bars + B_W * 8);
        float wt[4];
#pragma unroll
        for (int i = 0; i < 4; i++) wt[i] = lds1f(sb + S_ML + (sg + 16 * i) * 4);
#pragma unroll 1
        while (__any_sync(~0u, (or3(xo2(v[0].x, v[0].z, tg4[0]), xo2(v[1].x, v[1].z, tg4[1]), xo2(v[2].x, v[2].z, tg4[2])) | xo2(v[3].x, v[3].z, tg4[3])) & 1)) {
#pragma unroll
            for (int i = 0; i < 4; i++) if (xo2(v[i].x, v[i].z, tg4[i]) & 1) v[i] = ldr64x2(src[i]);
            SPIN_CHECK(it);
        }
        float acc[8] = {0.f, 0.f, 0.f, 0.f, 0.f, 0.f, 0.f, 0.f};
#pragma unroll
        for (int i = 0; i < 4; i++) {
            const uint32_t w[4] = {v[i].x & ~1u, v[i].y, v[i].z & ~1u, v[i].w};
#pragma unroll
            for (int k = 0; k < 4; k++) {
                acc[2 * k] = fmaf(wt[i], bflo(w[k]), acc[2 * k]);
                acc[2 * k + 1] = fmaf(wt[i], bfhi(w[k]), acc[2 * k + 1]);
            }
        }
        TS0(25);
        {
            const bool u16 = lane & 16, u8 = lane & 8;
            float r[4];
#pragma unroll
            for (int k = 0; k < 4; k++) r[k] = (u16 ? acc[k + 4] : acc[k]) + __shfl_xor_sync(~0u, u16 ? acc[k] : acc[k + 4], 16);
            const float t0 = (u8 ? r[2] : r[0]) + __shfl_xor_sync(~0u, u8 ? r[0] : r[2], 8);
            const float t1 = (u8 ? r[3] : r[1]) + __shfl_xor_sync(~0u, u8 ? r[1] : r[3], 8);
            uint32_t hi, lo; split2(t0, t1, hi, lo);
            const uint32_t a = sb + S_RED + wq * 320 + po + (u16 ? 8 : 0) + (u8 ? 4 : 0);
            sts1(a, hi); sts1(a + 4 * 320, lo);
        }
        bar_sync(2, 256);
        uint4 bq[4];
#pragma unroll
        for (int i = 0; i < 4; i++) bq[i] = lds4(sb + S_RED + g * 320 + i * 64 + q * 16);
        if (have != 15) { mbar_wait4(bars + C_WUV * 8); LOAD_UV(~have); }
        float d[4][4];
#pragma unroll
        for (int i = 0; i < 4; i++) {
            d[i][0] = d[i][1] = d[i][2] = d[i][3] = 0.f;
            mma16816(d[i], af[2 * i], bq[i].x, bq[i].y);
            mma16816(d[i], af[2 * i + 1], bq[i].z, bq[i].w);
        }
        const float r0 = ((d[0][0] + d[0][1]) + (d[1][0] + d[1][1])) + ((d[2][0] + d[2][1]) + (d[3][0] + d[3][1]));
        const float r1 = ((d[0][2] + d[0][3]) + (d[1][2] + d[1][3])) + ((d[2][2] + d[2][3]) + (d[3][2] + d[3][3]));
        float r = ((q & 1) ? r1 : r0) + __shfl_xor_sync(~0u, (q & 1) ? r0 : r1, 1);
        r += __shfl_xor_sync(~0u, r, 2);
        str1(d5, tagf(r, tg));
    }
    const uint32_t t_e = clk32();
    TS0(12);
    const unsigned char* sm[4];
    uint2 mm[6];
#pragma unroll
    for (int i = 0; i < 4; i++) sm[i] = sp + pick(G_MOD2 + i * 8192 + tid * 8, beta);
#define LOAD_MM() do { mm[0] = ldr2(sm[0]); mm[1] = ldr2(sm[0] + 2048); mm[2] = ldr2(sm[1]); mm[3] = ldr2(sm[2]); mm[4] = ldr2(sm[2] + 2048); mm[5] = ldr2(sm[3]); } while (0)
#define BAD_MM() or3(or3(bad2(mm[0], tg), bad2(mm[1], tg), bad2(mm[2], tg)), or3(bad2(mm[3], tg), bad2(mm[4], tg), bad2(mm[5], tg)), 0)
    {
        const int m = lane >> 3, r8 = lane & 7;
        const uint32_t a0 = sb + S_WO + (warp >> 1) * 2048 + ((m >> 1) * 8 + r8) * 64 + ((((warp & 1) * 2 + (m & 1)) ^ (r8 >> 1)) << 4);
        const unsigned char* src = sp + pick(G_H5 + spread(((b >> 4) * 4 + (warp >> 1)) * 2048 + (tid & 63) * 8), beta);
        uint2 c0, c1, c2, c3; int it = 0;
        uint32_t have = 0;
        unsigned char* d6 = sp + G_H6 + spread(b * 128 + lane * 4) + (warp & 1) * 4096;
        PIN(d6);
        wait_until(t_e, p.tm[D_H5]);
#pragma unroll 1
        do {
            c0 = ldr2(src); c1 = ldr2(src + 512); c2 = ldr2(src + 1024); c3 = ldr2(src + 1536);
            const uint32_t now = mbar_mask4(bars + C_WO * 8) & ~have;
#pragma unroll
            for (int i = 0; i < 4; i++)
                if (now >> i & 1) { ldsm4t(a0 + i * 8192, af[2 * i]); ldsm4t(a0 + i * 8192 + 1024, af[2 * i + 1]); }
            have |= now;
            SPIN_CHECK(it);
        } while (__any_sync(~0u, or3(or3(bad2(c0, tg), bad2(c1, tg), bad2(c2, tg)), bad2(c3, tg), 0) & 1));
        uint32_t hi, lo;
        split2((u2f(c0.x) + u2f(c1.x)) + (u2f(c2.x) + u2f(c3.x)), (u2f(c0.y) + u2f(c1.y)) + (u2f(c2.y) + u2f(c3.y)), hi, lo);
        const uint32_t a = sb + S_FVEC + (tid >> 4) * 128 + vpos((tid & 15) * 2);
        sts1(a, hi); sts1(a + 64, lo);
        TS0(14);
        bar_sync(2, 256);
        if (b < NFFN) LOAD_MM();
        uint4 bq[4];
#pragma unroll
        for (int i = 0; i < 4; i++) bq[i] = lds4(sb + S_FVEC + (i * 4 + (warp >> 1)) * 128 + vlane);
        if (have != 15) {
#pragma unroll
            for (int i = 0; i < 4; i++)
                if (!(have >> i & 1)) {
                    mbar_wait(bars + (C_WO + i) * 8);
                    ldsm4t(a0 + i * 8192, af[2 * i]); ldsm4t(a0 + i * 8192 + 1024, af[2 * i + 1]);
                }
        }
        float d[4][4];
#pragma unroll
        for (int i = 0; i < 4; i++) {
            d[i][0] = d[i][1] = d[i][2] = d[i][3] = 0.f;
            mma16816(d[i], af[2 * i], bq[i].x, bq[i].y);
            mma16816(d[i], af[2 * i + 1], bq[i].z, bq[i].w);
        }
        TS0(15);
        {
            const uint32_t o = sb + (q ? S_RED + tid * 4 : S_R16 + ((warp & 1) * 16 + g) * 16 + (warp >> 1) * 4);
            sts1f(o, ((d[0][0] + d[0][1]) + (d[1][0] + d[1][1])) + ((d[2][0] + d[2][1]) + (d[3][0] + d[3][1])));
            sts1f(o + 128, ((d[0][2] + d[0][3]) + (d[1][2] + d[1][3])) + ((d[2][2] + d[2][3]) + (d[3][2] + d[3][3])));
        }
        bar_sync(2, 256);
        if (tid < 64) {
            const float4 u = lds4f(sb + S_R16 + lane * 16);
            str1(d6, tagf((u.x + u.y) + (u.z + u.w), tg));
        }
        if (tid == 64) mbar_arrive(bars + B_F * 8);
        if (tid >= 224) str4(sp + G_H3 + (j * 2 + ((tid >> 3) & 1)) * 8192 + (tid & 16) * 256 + h * 128 + (tid & 7) * 16, 0, 0, 0, 0);
    }
    const uint32_t t_f = clk32();
    TS0(26);
    if (b < NFFN) {
        const uint32_t ga_ = sb + S_GVEC + (warp * 2 + (lane >> 4)) * 512 + vpos((lane & 15) * 2);
        TS0(16);
        const int m = lane >> 3, r8 = lane & 7;
        const uint32_t a0 = sb + S_W1 + warp * 2048 + ((m >> 1) * 8 + r8) * 32 + (((m & 1) ^ (r8 >> 2)) << 4);
        bool have1 = false;
        unsigned char* d7 = sp + G_H7 + (tid >> 2) * 8192 + b * 32 + (tid & 3) * 8;
        PIN(d7);
        float x20, x21;
        {
            const unsigned char* so[4];
#pragma unroll
            for (int i = 0; i < 4; i++) so[i] = sp + pick(G_H6 + i * 8192 + tid * 8, beta);
            uint2 c[8]; int it = 0;
            float g0, g1;
#define STAGE_MM() do { \
                g0 = 1.f + (u2f(mm[2].x) + u2f(mm[5].x)); g1 = 1.f + (u2f(mm[2].y) + u2f(mm[5].y)); \
                uint32_t hi, lo; \
                split2(g0, g1, hi, lo); sts1(ga_ + 128, hi); sts1(ga_ + 192, lo); \
                split2(u2f(mm[1].x) + u2f(mm[4].x), u2f(mm[1].y) + u2f(mm[4].y), hi, lo); sts1(ga_ + 256, hi); sts1(ga_ + 320, lo); } while (0)
#pragma unroll 1
            while (BAD_MM() & 1) { LOAD_MM(); SPIN_CHECK(it); }
            STAGE_MM();
            have1 = mbar_mask4(bars + C_W1 * 8) >> wg & 1;
            if (have1) {
#pragma unroll
                for (int i = 0; i < 4; i++) ldsm4t(a0 + i * 512, af[i]);
            }
            wait_until(t_f, p.tm[D_H6]);
#pragma unroll 1
            while (true) {
#pragma unroll
                for (int i = 0; i < 8; i++) c[i] = ldr2(so[i >> 1] + (i & 1) * 2048);
                uint32_t bc = 0;
                bc = or3(or3(bad2(c[0], tg), bad2(c[1], tg), bad2(c[2], tg)), or3(bad2(c[3], tg), bad2(c[4], tg), bad2(c[5], tg)),
                         or3(bad2(c[6], tg), bad2(c[7], tg), bc));
                if (!__any_sync(~0u, bc & 1)) break;
                SPIN_CHECK(it);
            }
            x20 = fmaf(u2f(mm[0].x) + u2f(mm[3].x),
                       ((u2f(c[0].x) + u2f(c[1].x)) + (u2f(c[2].x) + u2f(c[3].x))) + ((u2f(c[4].x) + u2f(c[5].x)) + (u2f(c[6].x) + u2f(c[7].x))), bflo(xw2));
            x21 = fmaf(u2f(mm[0].y) + u2f(mm[3].y),
                       ((u2f(c[0].y) + u2f(c[1].y)) + (u2f(c[2].y) + u2f(c[3].y))) + ((u2f(c[4].y) + u2f(c[5].y)) + (u2f(c[6].y) + u2f(c[7].y))), bfhi(xw2));
            uint32_t hi, lo;
            split2(x20 * g0, x21 * g1, hi, lo); sts1(ga_, hi); sts1(ga_ + 64, lo);
            split2(x20, x21, hi, lo); sts1(ga_ + 384, hi); sts1(ga_ + 448, lo);
            if ((tid >> 2) == b) sts2(sb + S_X2 + (tid & 3) * 8, __float_as_uint(x20), __float_as_uint(x21));
        }
        TS0(17);
        __syncwarp();
        const uint32_t va = sb + S_GVEC + warp * 1024 + g * 64 + q * 16;
        const uint4 bq0 = lds4(va), bq1 = lds4(va + 512);
        if (!have1) {
            mbar_wait(bars + (C_W1 + wg) * 8);
#pragma unroll
            for (int i = 0; i < 4; i++) ldsm4t(a0 + i * 512, af[i]);
        }
        float d0[4] = {0.f, 0.f, 0.f, 0.f}, d1[4] = {0.f, 0.f, 0.f, 0.f}, d2[4] = {0.f, 0.f, 0.f, 0.f}, d3[4] = {0.f, 0.f, 0.f, 0.f};
        mma16816(d0, af[0], bq0.x, bq0.y); mma16816(d1, af[1], bq0.z, bq0.w);
        mma16816(d2, af[2], bq1.x, bq1.y); mma16816(d3, af[3], bq1.z, bq1.w);
        float e0[4] = {0.f, 0.f, 0.f, 0.f}, e1[4] = {0.f, 0.f, 0.f, 0.f};
        {
            const uint32_t one = 0x3F803F80u;
            const uint32_t t0[4] = {bq0.x, one, bq0.y, one}, t1[4] = {bq0.z, one, bq0.w, one};
            const uint32_t t2[4] = {bq1.x, one, bq1.y, one}, t3[4] = {bq1.z, one, bq1.w, one};
            mma16816(e0, t0, bq0.x, bq0.y); mma16816(e1, t1, bq0.z, bq0.w);
            mma16816(e0, t2, bq1.x, bq1.y); mma16816(e1, t3, bq1.z, bq1.w);
        }
        {
            const bool st = q == 3;
            const float lo_ = fsel(st, (e0[0] + e0[1]) + (e1[0] + e1[1]), ((d0[0] + d0[1]) + (d1[0] + d1[1])) + ((d2[0] + d2[1]) + (d3[0] + d3[1])));
            const float hi_ = fsel(st, (e0[2] + e0[3]) + (e1[2] + e1[3]), ((d0[2] + d0[3]) + (d1[2] + d1[3])) + ((d2[2] + d2[3]) + (d3[2] + d3[3])));
            sts1f(sb + S_RED + q * 512 + g * 32 + warp * 4, lo_);
            sts1f(sb + S_RED + q * 512 + (g + 8) * 32 + warp * 4, hi_);
        }
        TS0(18);
        bar_arrive(9, 288);
        uint32_t w2r[16];
        mbar_wait2(bars + C_W2 * 8);
#pragma unroll
        for (int r = 0; r < 16; r++) w2r[r] = lds1(sb + S_W2 + r * 1024 + tid * 4);
        float w2f[32];
#pragma unroll
        for (int r = 0; r < 16; r++) { w2f[2 * r] = bflo(w2r[r]); w2f[2 * r + 1] = bfhi(w2r[r]); }
        bar_sync(10, b < 64 ? 320 : 288);
        float y0a = 0.f, y0b = 0.f, y1a = 0.f, y1b = 0.f;
#pragma unroll
        for (int r = 0; r < 16; r += 4) {
            const float4 f = lds4f(sb + S_STAT + r * 4);
            y0a = fmaf(f.x, w2f[2 * r], y0a); y1a = fmaf(f.x, w2f[2 * r + 1], y1a);
            y0b = fmaf(f.y, w2f[2 * r + 2], y0b); y1b = fmaf(f.y, w2f[2 * r + 3], y1b);
            y0a = fmaf(f.z, w2f[2 * r + 4], y0a); y1a = fmaf(f.z, w2f[2 * r + 5], y1a);
            y0b = fmaf(f.w, w2f[2 * r + 6], y0b); y1b = fmaf(f.w, w2f[2 * r + 7], y1b);
        }
        const uint32_t w0 = tagf(y0a + y0b, tg), w1 = tagf(y1a + y1b, tg);
        str2(d7, w0, w1); str2(d7 + 4096, w0, w1);
        TS0(19);
    }
}

__global__ void fb_gemv(const float* v, int vs, const __nv_bfloat16* W, size_t ws, size_t ks, size_t ns, int K, int N, float* out, float scale) {
    const int n = blockIdx.x * 8 + (threadIdx.x >> 5), z = blockIdx.y;
    if (n >= N) return;
    float s = 0.f;
    for (int k = threadIdx.x & 31; k < K; k += 32) s += v[(size_t)z * vs + k] * __bfloat162float(W[z * ws + k * ks + n * ns]);
    for (int o = 16; o; o >>= 1) s += __shfl_xor_sync(~0u, s, o);
    if ((threadIdx.x & 31) == 0) out[(size_t)z * N + n] = s * scale;
}
__device__ float fb_block_reduce(float v, bool mx, float* sh) {
    for (int o = 16; o; o >>= 1) { const float t = __shfl_xor_sync(~0u, v, o); v = mx ? fmaxf(v, t) : v + t; }
    __syncthreads();
    if ((threadIdx.x & 31) == 0) sh[threadIdx.x >> 5] = v;
    __syncthreads();
    v = sh[0];
    for (int i = 1; i < 16; i++) v = mx ? fmaxf(v, sh[i]) : v + sh[i];
    return v;
}
__global__ void fb_elem(int step, Params p, float* f) {
    __shared__ float sh[16];
    const int t = threadIdx.x;
    float* sc = f; float* mod = f + 512; float* hh = f + 4096; float* sco = f + 32768; float* o = f + 8192; float* x2 = f + 8704;
    float* ff = f + 9216; float* y = f + 11264;
    if (step == 0) { const float c = __bfloat162float(p.c[t]); sc[t] = c / (1.f + expf(-c)); }
    if (step == 1 || step == 3) {
        float x = __bfloat162float(p.x[t]);
        if (step == 3) { x += mod[1024 + t] * o[t]; x2[t] = x; }
        const float m = fb_block_reduce(x, false, sh) / 512.f, va = fb_block_reduce((x - m) * (x - m), false, sh) / 512.f;
        hh[t] = (x - m) * rsqrtf(va + 1e-5f) * (1.f + mod[(step == 1 ? 512 : 2048) + t]) + mod[(step == 1 ? 0 : 1536) + t];
    }
    if (step == 2) {
        float* r = sco + blockIdx.x * 8192;
        float m = -INFINITY, s = 0.f;
        for (int k = t; k < 8192; k += 512) m = fmaxf(m, r[k]);
        m = fb_block_reduce(m, true, sh);
        for (int k = t; k < 8192; k += 512) { r[k] = expf(r[k] - m); s += r[k]; }
        s = fb_block_reduce(s, false, sh);
        for (int k = t; k < 8192; k += 512) r[k] /= s;
    }
    if (step == 4)
        for (int n = t; n < 1376; n += 512) {
            const float a = ff[n] + __bfloat162float(p.b1[n]);
            ff[n] = 0.5f * a * (1.f + tanhf(0.7978845608f * (a + 0.044715f * a * a * a)));
        }
    if (step == 5) p.out[t] = __float2bfloat16(x2[t] + mod[2560 + t] * (y[t] + __bfloat162float(p.b2[t])));
}
void launch_fallback(const Params& p, void* const* d_in, cudaStream_t st) {
    typedef const __nv_bfloat16* W;
    float* f = reinterpret_cast<float*>(p.s + G_BYTES - (2 << 20) + 0);
    float *sc = f, *mod = f + 512, *hh = f + 4096, *q = f + 12288, *qa = f + 16384, *sco = f + 32768, *cc = f + 16384, *ctx = f + 12288;
    float *o = f + 8192, *ff = f + 9216, *y = f + 11264;
    fb_elem<<<1, 512, 0, st>>>(0, p, f);
    fb_gemv<<<dim3(384, 1), 256, 0, st>>>(sc, 0, (W)d_in[12], 0, 3072, 1, 512, 3072, mod, 1.f);
    fb_elem<<<1, 512, 0, st>>>(1, p, f);
    fb_gemv<<<dim3(512, 1), 256, 0, st>>>(hh, 0, (W)d_in[2], 0, 4096, 1, 512, 4096, q, 1.f);
    fb_gemv<<<dim3(64, 32), 256, 0, st>>>(q, 128, (W)d_in[3], 128, 1, 4096, 128, 512, qa, 0.08838834764831845f);
    fb_gemv<<<dim3(1024, 32), 256, 0, st>>>(qa, 512, (W)d_in[1], 0, 1, 512, 512, 8192, sco, 1.f);
    fb_elem<<<32, 512, 0, st>>>(2, p, f);
    fb_gemv<<<dim3(64, 32), 256, 0, st>>>(sco, 8192, (W)d_in[1], 0, 512, 1, 8192, 512, cc, 1.f);
    fb_gemv<<<dim3(16, 32), 256, 0, st>>>(cc, 512, (W)d_in[4], 128, 4096, 1, 512, 128, ctx, 1.f);
    fb_gemv<<<dim3(64, 1), 256, 0, st>>>(ctx, 0, (W)d_in[5], 0, 512, 1, 4096, 512, o, 1.f);
    fb_elem<<<1, 512, 0, st>>>(3, p, f);
    fb_gemv<<<dim3(172, 1), 256, 0, st>>>(hh, 0, (W)d_in[7], 0, 1376, 1, 512, 1376, ff, 1.f);
    fb_elem<<<1, 512, 0, st>>>(4, p, f);
    fb_gemv<<<dim3(64, 1), 256, 0, st>>>(ff, 0, (W)d_in[9], 0, 512, 1, 1376, 512, y, 1.f);
    fb_elem<<<1, 512, 0, st>>>(5, p, f);
}

typedef CUresult (*EncodeFn)(CUtensorMap*, CUtensorMapDataType, cuuint32_t, void*, const cuuint64_t*, const cuuint64_t*,
                             const cuuint32_t*, const cuuint32_t*, CUtensorMapInterleave, CUtensorMapSwizzle,
                             CUtensorMapL2promotion, CUtensorMapFloatOOBfill);

void make_map(EncodeFn enc, CUtensorMap* m, const void* ptr, uint64_t d0, uint64_t d1, uint64_t d2, uint64_t d3,
              uint64_t s1, uint64_t s2, uint64_t s3, uint32_t b0, uint32_t b1, uint32_t b2, uint32_t b3, CUtensorMapSwizzle sw) {
    cuuint64_t dims[4] = {d0, d1, d2, d3};
    cuuint64_t st[3] = {s1, s2, s3};
    cuuint32_t box[4] = {b0, b1, b2, b3};
    cuuint32_t es[4] = {1, 1, 1, 1};
    enc(m, CU_TENSOR_MAP_DATA_TYPE_BFLOAT16, 4, const_cast<void*>(ptr), dims, st, box, es, CU_TENSOR_MAP_INTERLEAVE_NONE, sw,
        CU_TENSOR_MAP_L2_PROMOTION_L2_128B, CU_TENSOR_MAP_FLOAT_OOB_FILL_NONE);
}

uint16_t g_tm[NTM] = {3780,7540,14680,280,270,600,700,260};
uint16_t g_sched[34] = {0,1070,1644,2193,2767,3341,3975,4524,5098,5672,6246,6820,7394,7993,8567,9081,9201,
                        9449,9449,9899,10199,10999,12439,12999,14829,14849,14919,16089,16889,17929,18009,18799,18889,0};

}

extern "C" void kernel_launch(void* const* d_in, const int* in_sizes, int n_in, void* d_out, int out_size) {
    (void)in_sizes; (void)n_in; (void)out_size;
    static EncodeFn enc = nullptr;
    static unsigned char* scratch = nullptr;
    static bool fused_ok = false;
    if (!scratch) {
        cudaGetSymbolAddress((void**)&scratch, g_scratch);
        scratch = (unsigned char*)(((uintptr_t)scratch + (2 << 20) - 1) & ~(uintptr_t)((2 << 20) - 1));
        void* fn = nullptr;
        cudaDriverEntryPointQueryResult qr;
        cudaGetDriverEntryPoint("cuTensorMapEncodeTiled", &fn, cudaEnableDefault, &qr);
        enc = (EncodeFn)fn;
        int clusters = 0;
        if (enc && cudaFuncSetAttribute(fused_decode_kernel, cudaFuncAttributeMaxDynamicSharedMemorySize, SMEM_BYTES) == cudaSuccess) {
            cudaLaunchConfig_t cfg = {};
            cfg.gridDim = dim3(NCTA); cfg.blockDim = dim3(NTHR); cfg.dynamicSmemBytes = SMEM_BYTES;
            cudaLaunchAttribute at[1];
            at[0].id = cudaLaunchAttributeClusterDimension; at[0].val.clusterDim.x = 2; at[0].val.clusterDim.y = 1; at[0].val.clusterDim.z = 1;
            cfg.attrs = at; cfg.numAttrs = 1;
            if (cudaOccupancyMaxActiveClusters(&clusters, fused_decode_kernel, &cfg) != cudaSuccess) clusters = 0;
        }
        (void)cudaGetLastError();
        fused_ok = clusters >= NCTA / 2;
    }
    Params p = {};
    p.x = (const __nv_bfloat16*)d_in[0];
    p.c = (const __nv_bfloat16*)d_in[11];
    p.b1 = (const __nv_bfloat16*)d_in[8];
    p.b2 = (const __nv_bfloat16*)d_in[10];
    p.out = (__nv_bfloat16*)d_out;
    p.s = scratch;
    for (int i = 0; i < NTM; i++) p.tm[i] = g_tm[i];
    for (int i = 0; i < 34; i++) p.sched[i] = g_sched[i];
    if (!fused_ok) { launch_fallback(p, d_in, cudaStreamPerThread); return; }
    const auto S128 = CU_TENSOR_MAP_SWIZZLE_128B, S32 = CU_TENSOR_MAP_SWIZZLE_32B, S64 = CU_TENSOR_MAP_SWIZZLE_64B, S0 = CU_TENSOR_MAP_SWIZZLE_NONE;
    make_map(enc, &p.m[0], d_in[12], 3072, 512, 1, 1, 6144, 6144 * 512, 6144 * 512, 16, 256, 1, 1, S32);
    make_map(enc, &p.m[1], d_in[2], 64, 512, 64, 1, 8192, 128, 8192 * 512, 64, 32, 2, 1, S128);
    make_map(enc, &p.m[2], d_in[3], 64, 512, 64, 1, 8192, 128, 8192 * 512, 64, 32, 2, 1, S128);
    make_map(enc, &p.m[3], d_in[1], 64, 8192, 8, 1, 1024, 128, 1024 * 8192, 64, 64, 1, 1, S128);
    make_map(enc, &p.m[4], d_in[4], 64, 64, 8, 64, 8192, 8192 * 64, 128, 64, 16, 2, 2, S128);
    make_map(enc, &p.m[5], d_in[5], 512, 4096, 1, 1, 1024, 1024 * 4096, 1024 * 4096, 32, 128, 1, 1, S64);
    make_map(enc, &p.m[8], d_in[12], 3072, 512, 1, 1, 6144, 6144 * 512, 6144 * 512, 32, 128, 1, 1, S64);
    make_map(enc, &p.m[6], d_in[7], 1376, 512, 1, 1, 2752, 2752 * 512, 2752 * 512, 16, 256, 1, 1, S32);
    make_map(enc, &p.m[7], d_in[9], 256, 2752, 1, 1, 512, 512 * 2752, 512 * 2752, 256, 16, 1, 1, S0);
    fused_decode_kernel<<<NCTA, NTHR, SMEM_BYTES, cudaStreamPerThread>>>(p);
}
```

```cpp
#include <cuda_runtime.h>
#include <cuda_bf16.h>
#include <cuda.h>
#include <stdint.h>

namespace {

constexpr int NCTA   = 128;
constexpr int NFFN   = 86;
constexpr int NCHUNK = 33;
constexpr int NTHR   = 384;

constexpr int C_MOD1 = 0, C_WQ = 1, C_WUK = 5, C_CKV = 9, C_T1 = 15, C_WUV = 19, C_W1 = 29, C_W2 = 31;
constexpr int C_MOD2 = 23, C_WO = 25;

constexpr int S_WQ   = 0;
constexpr int S_WUK  = 32768;
constexpr int S_CKV  = 65536;
constexpr int S_WUV  = 131072;
constexpr int S_WO   = 163840;
constexpr int S_MOD2 = 196608;
constexpr int S_MOD1 = 212992;
constexpr int S_SC   = 221184;
constexpr int S_RED  = 223232;
constexpr int S_VEC  = 227328;
constexpr int S_R16  = 227840;
constexpr int S_MAX  = 228352;
constexpr int S_ONES = 229376;
constexpr int S_ML   = 230400;
constexpr int S_X2   = 230400 + 384;
constexpr int S_STAT = 230912;
constexpr int S_BAR  = 230976;
constexpr int S_EP   = 231312;
constexpr int S_B4   = 230912;
constexpr int S_TS   = 231328;
constexpr int S_END  = 231712;
constexpr int S_QABS = S_WQ, S_XBUF1 = S_WQ + 24576, S_XBUF0 = S_MOD1, S_XCH = S_WUK, S_GVEC = S_WQ, S_FVEC = S_WQ + 8192;
constexpr int S_W1 = S_WUK, S_W2 = S_WUK + 16384, S_P = S_MOD1;
constexpr int B_UK = 33, B_QK = 34, B_X = 35, B_F = 37, B_BETA = 38, B_BETA4 = 39, B_W = 40, B_O = 41, NBAR = 42;
constexpr int SMEM_BYTES = S_END;

#define WARM 120
#define WARM_T0 4200
constexpr int WIN = 5;
enum { T_H1 = 0, T_H3, T_H4, D_H5, D_H6, D_H7, D_H4, A_H4, NTM = 8 };

constexpr uint32_t G_H1 = 0;
constexpr uint32_t G_H6 = 192 << 10;
constexpr uint32_t G_MOD2 = 16 << 10;
constexpr uint32_t G_ML = 48 << 10;
constexpr uint32_t G_PROBE = 88 << 10;
constexpr uint32_t G_H3 = 128 << 10;
constexpr uint32_t G_H2 = 256 << 10;
constexpr uint32_t G_H5 = 384 << 10;
constexpr uint32_t G_H7 = 512 << 10;
constexpr uint32_t G_EPOCH = 1 << 20;
constexpr uint32_t G_TS = (1 << 20) + 4096;
constexpr uint32_t G_H4 = 2 << 20;
constexpr uint32_t G_BYTES = 10 << 20;
__device__ __align__(256) unsigned char g_scratch[G_BYTES + (2 << 20)];
__device__ __forceinline__ uint32_t spread(uint32_t o) { return o + (o & ~4095u); }
__device__ __forceinline__ uint32_t pick(uint32_t po, uint32_t beta) {
    return po + (((beta ^ __popc(po & 0xB2000u)) & 1u) << 12);
}
#define TS(i) do {} while (0)
#define TS0(i) do {} while (0)
#define TS4(i) do {} while (0)

struct Params {
    const __nv_bfloat16* x;
    const __nv_bfloat16* c;
    const __nv_bfloat16* b1;
    const __nv_bfloat16* b2;
    __nv_bfloat16* out;
    unsigned char* s;
    uint16_t tm[NTM];
    uint16_t sched[34];
    CUtensorMap m[9];
};

constexpr uint64_t POL_FIRST = 0x12F0000000000000ull, POL_NORMAL = 0x16F0000000000000ull;
constexpr int SPIN_MAX = 1 << 21;

__device__ __forceinline__ void mbar_init(uint32_t bar, uint32_t cnt) {
    asm volatile("mbarrier.init.shared::cta.b64 [%0], %1;" ::"r"(bar), "r"(cnt) : "memory");
}
__device__ __forceinline__ void mbar_expect_tx(uint32_t bar, uint32_t bytes) {
    asm volatile("mbarrier.arrive.expect_tx.shared::cta.b64 _, [%0], %1;" ::"r"(bar), "r"(bytes) : "memory");
}
__device__ __forceinline__ void mbar_arrive(uint32_t bar) {
    asm volatile("mbarrier.arrive.shared::cta.b64 _, [%0];" ::"r"(bar) : "memory");
}
__device__ __forceinline__ void mbar_wait(uint32_t bar) {
    asm volatile("{\n.reg .pred p;\nW:\nmbarrier.try_wait.parity.shared::cta.b64 p, [%0], 0;\n@!p bra W;\n}" ::"r"(bar) : "memory");
}
__device__ __forceinline__ void mbar_wait2(uint32_t bar) {
    asm volatile("{\n.reg .pred p, q;\nW:\n"
                 "mbarrier.try_wait.parity.shared::cta.b64 p, [%0], 0;\n"
                 "mbarrier.try_wait.parity.shared::cta.b64 q, [%0+8], 0;\n"
                 "and.pred p, p, q;\n@!p bra W;\n}" ::"r"(bar) : "memory");
}
__device__ __forceinline__ void mbar_wait4(uint32_t bar) {
    asm volatile("{\n.reg .pred p, q, r, s;\nW:\n"
                 "mbarrier.try_wait.parity.shared::cta.b64 p, [%0], 0;\n"
                 "mbarrier.try_wait.parity.shared::cta.b64 q, [%0+8], 0;\n"
                 "mbarrier.try_wait.parity.shared::cta.b64 r, [%0+16], 0;\n"
                 "mbarrier.try_wait.parity.shared::cta.b64 s, [%0+24], 0;\n"
                 "and.pred p, p, q;\nand.pred r, r, s;\nand.pred p, p, r;\n@!p bra W;\n}" ::"r"(bar) : "memory");
}
__device__ __forceinline__ void mbar_wait_cluster(uint32_t bar) {
    asm volatile("{\n.reg .pred p;\nW:\nmbarrier.try_wait.parity.acquire.cluster.shared::cta.b64 p, [%0], 0;\n@!p bra W;\n}" ::"r"(bar) : "memory");
}
__device__ __forceinline__ void tma4(uint32_t dst, const CUtensorMap* m, int c0, int c1, int c2, int c3, uint32_t bar, uint64_t pol) {
    asm volatile("cp.async.bulk.tensor.4d.shared::cluster.global.mbarrier::complete_tx::bytes.L2::cache_hint [%0], [%1, {%3,%4,%5,%6}], [%2], %7;"
                 ::"r"(dst), "l"(m), "r"(bar), "r"(c0), "r"(c1), "r"(c2), "r"(c3), "l"(pol) : "memory");
}
__device__ __forceinline__ void bar_sync(int id, int n) { asm volatile("bar.sync %0, %1;" ::"r"(id), "r"(n) : "memory"); }
__device__ __forceinline__ void bar_arrive(int id, int n) { asm volatile("bar.arrive %0, %1;" ::"r"(id), "r"(n) : "memory"); }
__device__ __forceinline__ void fence_async() { asm volatile("fence.proxy.async.shared::cta;" ::: "memory"); }

__device__ __forceinline__ uint32_t ldr1(const void* p) {
    uint32_t v; asm volatile("ld.relaxed.gpu.global.u32 %0, [%1];" : "=r"(v) : "l"(p) : "memory"); return v;
}
__device__ __forceinline__ uint2 ldr2(const void* p) {
    uint2 v; asm volatile("ld.relaxed.gpu.global.v2.u32 {%0,%1}, [%2];" : "=r"(v.x), "=r"(v.y) : "l"(p) : "memory"); return v;
}
__device__ __forceinline__ uint4 ldr4(const void* p) {
    uint4 v; asm volatile("ld.relaxed.gpu.global.v4.u32 {%0,%1,%2,%3}, [%4];"
                          : "=r"(v.x), "=r"(v.y), "=r"(v.z), "=r"(v.w) : "l"(p) : "memory"); return v;
}
__device__ __forceinline__ void str1(void* p, uint32_t v) { asm volatile("st.relaxed.gpu.global.u32 [%0], %1;" ::"l"(p), "r"(v) : "memory"); }
__device__ __forceinline__ void str2(void* p, uint32_t a, uint32_t b) {
    asm volatile("st.relaxed.gpu.global.v2.u32 [%0], {%1,%2};" ::"l"(p), "r"(a), "r"(b) : "memory");
}
__device__ __forceinline__ void str4(void* p, uint32_t a, uint32_t b, uint32_t c, uint32_t d) {
    asm volatile("st.relaxed.gpu.global.v4.u32 [%0], {%1,%2,%3,%4};" ::"l"(p), "r"(a), "r"(b), "r"(c), "r"(d) : "memory");
}
__device__ __forceinline__ void str64(void* p, uint32_t a, uint32_t b) {
    asm volatile("{\n.reg .b64 t;\nmov.b64 t, {%1,%2};\nst.relaxed.gpu.global.b64 [%0], t;\n}" ::"l"(p), "r"(a), "r"(b) : "memory");
}
__device__ __forceinline__ uint4 ldr64x2(const void* p) {
    uint4 v; asm volatile("{\n.reg .b64 s, t;\nld.relaxed.gpu.global.v2.b64 {s,t}, [%4];\nmov.b64 {%0,%1}, s;\nmov.b64 {%2,%3}, t;\n}"
                          : "=r"(v.x), "=r"(v.y), "=r"(v.z), "=r"(v.w) : "l"(p) : "memory"); return v;
}
__device__ __forceinline__ uint32_t tagf(float v, uint32_t tg) {
    uint32_t r; asm("lop3.b32 %0, %1, 0xFFFFFFFE, %2, 0xEA;" : "=r"(r) : "r"(__float_as_uint(v)), "r"(tg)); return r;
}
__device__ __forceinline__ float u2f(uint32_t v) { return __uint_as_float(v); }

__device__ __forceinline__ void sts1(uint32_t a, uint32_t v) { asm volatile("st.shared.u32 [%0], %1;" ::"r"(a), "r"(v) : "memory"); }
__device__ __forceinline__ void sts1f(uint32_t a, float v) { asm volatile("st.shared.f32 [%0], %1;" ::"r"(a), "f"(v) : "memory"); }
__device__ __forceinline__ void stsh(uint32_t a, uint32_t v) { asm volatile("st.shared.u16 [%0], %1;" ::"r"(a), "h"((unsigned short)v) : "memory"); }
__device__ __forceinline__ void sts2(uint32_t a, uint32_t x, uint32_t y) { asm volatile("st.shared.v2.u32 [%0], {%1,%2};" ::"r"(a), "r"(x), "r"(y) : "memory"); }
__device__ __forceinline__ void sts4(uint32_t a, uint32_t x, uint32_t y, uint32_t z, uint32_t w) {
    asm volatile("st.shared.v4.u32 [%0], {%1,%2,%3,%4};" ::"r"(a), "r"(x), "r"(y), "r"(z), "r"(w) : "memory");
}
__device__ __forceinline__ uint32_t lds1(uint32_t a) { uint32_t v; asm volatile("ld.shared.u32 %0, [%1];" : "=r"(v) : "r"(a) : "memory"); return v; }
__device__ __forceinline__ float lds1f(uint32_t a) { float v; asm volatile("ld.shared.f32 %0, [%1];" : "=f"(v) : "r"(a) : "memory"); return v; }
__device__ __forceinline__ float2 lds2f(uint32_t a) { float2 v; asm volatile("ld.shared.v2.f32 {%0,%1}, [%2];" : "=f"(v.x), "=f"(v.y) : "r"(a) : "memory"); return v; }
__device__ __forceinline__ uint4 lds4(uint32_t a) {
    uint4 v; asm volatile("ld.shared.v4.u32 {%0,%1,%2,%3}, [%4];" : "=r"(v.x), "=r"(v.y), "=r"(v.z), "=r"(v.w) : "r"(a) : "memory"); return v;
}
__device__ __forceinline__ float4 lds4f(uint32_t a) {
    float4 v; asm volatile("ld.shared.v4.f32 {%0,%1,%2,%3}, [%4];" : "=f"(v.x), "=f"(v.y), "=f"(v.z), "=f"(v.w) : "r"(a) : "memory"); return v;
}
__device__ __forceinline__ void ldsm4(uint32_t a, uint32_t (&r)[4]) {
    asm volatile("ldmatrix.sync.aligned.m8n8.x4.shared.b16 {%0,%1,%2,%3}, [%4];"
                 : "=r"(r[0]), "=r"(r[1]), "=r"(r[2]), "=r"(r[3]) : "r"(a) : "memory");
}
__device__ __forceinline__ void ldsm4t(uint32_t a, uint32_t (&r)[4]) {
    asm volatile("ldmatrix.sync.aligned.m8n8.x4.trans.shared.b16 {%0,%1,%2,%3}, [%4];"
                 : "=r"(r[0]), "=r"(r[1]), "=r"(r[2]), "=r"(r[3]) : "r"(a) : "memory");
}
__device__ __forceinline__ void stsm4t(uint32_t a, uint32_t r0, uint32_t r1, uint32_t r2, uint32_t r3) {
    asm volatile("stmatrix.sync.aligned.m8n8.x4.trans.shared.b16 [%0], {%1,%2,%3,%4};"
                 ::"r"(a), "r"(r0), "r"(r1), "r"(r2), "r"(r3) : "memory");
}
__device__ __forceinline__ void mma16816(float (&d)[4], const uint32_t (&a)[4], uint32_t b0, uint32_t b1) {
    asm volatile("mma.sync.aligned.m16n8k16.row.col.f32.bf16.bf16.f32 {%0,%1,%2,%3}, {%4,%5,%6,%7}, {%8,%9}, {%0,%1,%2,%3};"
                 : "+f"(d[0]), "+f"(d[1]), "+f"(d[2]), "+f"(d[3])
                 : "r"(a[0]), "r"(a[1]), "r"(a[2]), "r"(a[3]), "r"(b0), "r"(b1));
}
__device__ __forceinline__ uint32_t packbf(float lo, float hi) {
    uint32_t r; asm("cvt.rn.bf16x2.f32 %0, %1, %2;" : "=r"(r) : "f"(hi), "f"(lo)); return r;
}
__device__ __forceinline__ float bflo(uint32_t w) { return __uint_as_float(w << 16); }
__device__ __forceinline__ float bfhi(uint32_t w) { return __uint_as_float(w & 0xffff0000u); }
__device__ __forceinline__ void split2(float a, float b, uint32_t& hi, uint32_t& lo) {
    hi = packbf(a, b);
    lo = packbf(a - bflo(hi), b - bfhi(hi));
}
__device__ __forceinline__ uint32_t ordf(uint32_t u) { return u ^ ((uint32_t)((int)u >> 31) & 0x7FFFFFFFu); }
__device__ __forceinline__ void red_max(uint32_t a, uint32_t v) { asm volatile("red.shared.max.s32 [%0], %1;" ::"r"(a), "r"(v) : "memory"); }
__device__ __forceinline__ float fsel(bool c, float a, float b) {
    float r; asm("{\n.reg .pred p;\nsetp.ne.b32 p, %3, 0;\nselp.f32 %0, %1, %2, p;\n}" : "=f"(r) : "f"(a), "f"(b), "r"((int)c)); return r;
}
__device__ __forceinline__ float ex2(float x) { float y; asm("ex2.approx.ftz.f32 %0, %1;" : "=f"(y) : "f"(x)); return y; }

__device__ __forceinline__ int vpos(int k32) {
    return (((k32 & 7) >> 1) * 8 + (k32 >> 4) * 4 + ((k32 >> 3) & 1) * 2 + (k32 & 1)) * 2;
}

__device__ __forceinline__ void wg_fence()  { asm volatile("wgmma.fence.sync.aligned;" ::: "memory"); }
__device__ __forceinline__ void wg_commit() { asm volatile("wgmma.commit_group.sync.aligned;" ::: "memory"); }
template <int N> __device__ __forceinline__ void wg_wait() { asm volatile("wgmma.wait_group.sync.aligned %0;" ::"n"(N) : "memory"); }
__device__ __forceinline__ uint64_t mkdesc(uint32_t addr) {
    return (uint64_t)((addr & 0x3FFFF) >> 4) | ((uint64_t)64 << 16) | ((uint64_t)64 << 32) | ((uint64_t)1 << 62);
}
template <int TA>
__device__ __forceinline__ void wgmma_n32(float (&d)[16], uint64_t da, uint64_t db, int acc) {
    asm volatile("{\n.reg .pred p;\nsetp.ne.b32 p, %18, 0;\n"
                 "wgmma.mma_async.sync.aligned.m64n32k16.f32.bf16.bf16 "
                 "{%0,%1,%2,%3,%4,%5,%6,%7,%8,%9,%10,%11,%12,%13,%14,%15}, %16, %17, p, 1, 1, %19, 0;\n}"
                 : "+f"(d[0]), "+f"(d[1]), "+f"(d[2]), "+f"(d[3]), "+f"(d[4]), "+f"(d[5]), "+f"(d[6]), "+f"(d[7]),
                   "+f"(d[8]), "+f"(d[9]), "+f"(d[10]), "+f"(d[11]), "+f"(d[12]), "+f"(d[13]), "+f"(d[14]), "+f"(d[15])
                 : "l"(da), "l"(db), "r"(acc), "n"(TA));
}
__device__ __forceinline__ void reg_fence16(float (&d)[16]) {
#pragma unroll
    for (int i = 0; i < 16; i++) asm volatile("" : "+f"(d[i])::"memory");
}

template <bool TRANS>
__device__ __forceinline__ void gemv128(uint32_t tile, uint32_t vec, uint32_t bars, int warp, int lane, float& r0, float& r1) {
    const int m = lane >> 3, r8 = lane & 7;
    uint32_t bq[4][4];
#pragma unroll
    for (int i = 0; i < 4; i++) {
        uint4 t = lds4(vec + i * 128 + ((lane >> 2) & 1) * 64 + (lane & 3) * 16);
        bq[i][0] = t.x; bq[i][1] = t.y; bq[i][2] = t.z; bq[i][3] = t.w;
    }
    float d0[4] = {0.f, 0.f, 0.f, 0.f}, d1[4] = {0.f, 0.f, 0.f, 0.f};
    if (TRANS) {
        const uint32_t a0 = tile + (warp >> 2) * 4096 + ((m >> 1) * 8 + r8) * 128 + ((((warp & 3) * 2 + (m & 1)) ^ r8) << 4);
#pragma unroll
        for (int i = 0; i < 4; i++) {
            mbar_wait(bars + i * 8);
            uint32_t a[4], c[4];
            ldsm4t(a0 + i * 8192, a);
            ldsm4t(a0 + i * 8192 + 2048, c);
            mma16816(d0, a, bq[i][0], bq[i][1]);
            mma16816(d1, c, bq[i][2], bq[i][3]);
        }
    } else {
        mbar_wait(bars + (warp >> 1) * 8);
        const uint32_t a0 = tile + (warp >> 1) * 8192 + ((warp & 1) * 16 + (m & 1) * 8 + r8) * 128;
#pragma unroll
        for (int i = 0; i < 4; i++) {
            uint32_t a[4], c[4];
            ldsm4(a0 + (i >> 1) * 4096 + ((((i & 1) * 4 + (m >> 1)) ^ r8) << 4), a);
            ldsm4(a0 + (i >> 1) * 4096 + ((((i & 1) * 4 + 2 + (m >> 1)) ^ r8) << 4), c);
            mma16816(d0, a, bq[i][0], bq[i][1]);
            mma16816(d1, c, bq[i][2], bq[i][3]);
        }
    }
    r0 = (d0[0] + d0[1]) + (d1[0] + d1[1]);
    r1 = (d0[2] + d0[3]) + (d1[2] + d1[3]);
}

__device__ __forceinline__ void step32(uint32_t rows, uint32_t vecaddr, int lane, float (&d0)[4], float (&d1)[4]) {
    const int m = lane >> 3, r8 = lane & 7;
    const uint32_t a0 = rows + ((m >> 1) * 8 + r8) * 32 + (((m & 1) ^ (r8 >> 2)) << 4);
    uint4 t = lds4(vecaddr);
    uint32_t a[4], c[4];
    ldsm4t(a0, a);
    ldsm4t(a0 + 512, c);
    mma16816(d0, a, t.x, t.y);
    mma16816(d1, c, t.z, t.w);
}

__device__ __forceinline__ void reduce16_publish(uint32_t sb, float (&d0)[4], float (&d1)[4], int tid, int warp, int lane, unsigned char* dst, uint32_t tg) {
    if ((lane & 3) == 0) {
        sts1f(sb + S_R16 + (lane >> 2) * 32 + warp * 4, (d0[0] + d0[1]) + (d1[0] + d1[1]));
        sts1f(sb + S_R16 + ((lane >> 2) + 8) * 32 + warp * 4, (d0[2] + d0[3]) + (d1[2] + d1[3]));
    }
    bar_sync(2, 256);
    if (tid < 32) {
        float4 u = lds4f(sb + S_R16 + (tid & 15) * 32), v = lds4f(sb + S_R16 + (tid & 15) * 32 + 16);
        str1(dst + (tid & 15) * 4 + (tid >> 4) * 4096, tagf(((u.x + u.y) + (u.z + u.w)) + ((v.x + v.y) + (v.z + v.w)), tg));
    }
}

__device__ __forceinline__ uint32_t xo2(uint32_t a, uint32_t b, uint32_t t) {
    uint32_t r; asm("lop3.b32 %0, %1, %2, %3, 0x7E;" : "=r"(r) : "r"(a), "r"(b), "r"(t)); return r;
}
__device__ __forceinline__ uint32_t or3(uint32_t a, uint32_t b, uint32_t c) {
    uint32_t r; asm("lop3.b32 %0, %1, %2, %3, 0xFE;" : "=r"(r) : "r"(a), "r"(b), "r"(c)); return r;
}
__device__ __forceinline__ uint32_t bad2(const uint2& v, uint32_t tg) { return xo2(v.x, v.y, tg); }
__device__ __forceinline__ uint32_t bad4(const uint4& v, uint32_t tg) { return or3(xo2(v.x, v.y, tg), xo2(v.z, v.w, tg), 0); }
__device__ __forceinline__ bool nz4(const uint4& v) { return v.x != 0 && v.y != 0 && v.z != 0 && v.w != 0; }
__device__ __forceinline__ uint32_t clk32() { uint32_t c; asm volatile("mov.u32 %0, %%clock;" : "=r"(c)); return c; }
__device__ __forceinline__ void wait_until(uint32_t t0, uint32_t dt) {
#pragma unroll 1
    while ((int)(clk32() - t0 - dt) < 0) {}
}
__device__ __forceinline__ uint32_t mbar_mask4(uint32_t bar) {
    uint32_t m;
    asm volatile("{\n.reg .pred p, q, r, s;\n.reg .b32 a, b;\n"
                 "mbarrier.test_wait.parity.shared::cta.b64 p, [%1], 0;\n"
                 "mbarrier.test_wait.parity.shared::cta.b64 q, [%1+8], 0;\n"
                 "mbarrier.test_wait.parity.shared::cta.b64 r, [%1+16], 0;\n"
                 "mbarrier.test_wait.parity.shared::cta.b64 s, [%1+24], 0;\n"
                 "selp.u32 a, 1, 0, p;\nselp.u32 b, 2, 0, q;\nor.b32 a, a, b;\nselp.u32 b, 4, 0, r;\nor.b32 a, a, b;\n"
                 "selp.u32 b, 8, 0, s;\nor.b32 a, a, b;\nredux.sync.and.b32 %0, a, 0xffffffff;\n}" : "=r"(m) : "r"(bar) : "memory");
    return m;
}
__device__ __forceinline__ uint32_t probe_near(unsigned char* sp, uint32_t po, uint32_t sink) {
    uint32_t best0 = ~0u, best1 = ~0u;
#pragma unroll 1
    for (int r = 0; r < 5; r++) {
        uint32_t v; const uint32_t t0 = clk32();
        asm volatile("atom.relaxed.gpu.global.exch.b32 %0, [%1], %2;" : "=r"(v) : "l"(sp + po + (r & 1) * 4096), "r"(r) : "memory");
        sts1(sink, v);
        const uint32_t dt = clk32() - t0;
        if (r & 1) best1 = min(best1, dt); else best0 = min(best0, dt);
    }
    return (uint32_t)(best1 < best0) ^ (__popc(po & 0xB2000u) & 1u);
}
#define PIN(x) asm volatile("" : "+l"(x))
#define SPIN_CHECK(it) if (++(it) > SPIN_MAX) __trap()

__device__ __forceinline__ void mod2_tile(uint32_t sb, unsigned char* sp, uint32_t bars, int b, int nt, int lane, uint32_t tg) {
    const int m = lane >> 3, r8 = lane & 7, q = lane & 3;
    const uint32_t a0 = sb + S_MOD2 + ((m >> 1) * 8 + r8) * 64 + (((nt * 2 + (m & 1)) ^ (r8 >> 1)) << 4);
    const uint32_t v0 = sb + S_SC + (b >> 6) * 1024 + ((lane >> 2) & 1) * 64 + q * 16;
    float d0[4] = {0.f, 0.f, 0.f, 0.f}, d1[4] = {0.f, 0.f, 0.f, 0.f};
#pragma unroll 1
    for (int c = 0; c < 2; c++) {
        mbar_wait(bars + (C_MOD2 + c) * 8);
#pragma unroll
        for (int i = 0; i < 4; i++) {
            const uint4 t = lds4(v0 + (c * 4 + i) * 128);
            uint32_t a[4], e[4];
            ldsm4t(a0 + c * 8192 + i * 2048, a); ldsm4t(a0 + c * 8192 + i * 2048 + 1024, e);
            mma16816(d0, a, t.x, t.y); mma16816(d1, e, t.z, t.w);
        }
    }
    const float r0 = (d0[0] + d0[1]) + (d1[0] + d1[1]), r1 = (d0[2] + d0[3]) + (d1[2] + d1[3]);
    const float t0 = __shfl_sync(~0u, r0, lane & 28), t1 = __shfl_sync(~0u, r1, lane & 28);
    str1(sp + G_MOD2 + spread(b * 128 + nt * 64 + (q & 1) * 32 + (lane >> 2) * 4) + (q >> 1) * 4096, tagf((q & 1) ? t1 : t0, tg));
}

__global__ void __cluster_dims__(2, 1, 1) __launch_bounds__(NTHR, 1) fused_decode_kernel(const __grid_constant__ Params p) {
    extern __shared__ __align__(1024) unsigned char smem_raw[];
    const uint32_t sb = (uint32_t)__cvta_generic_to_shared(smem_raw);
    const int tid = threadIdx.x, lane = tid & 31;
    const int warp = __shfl_sync(~0u, tid >> 5, 0);
    const int b = blockIdx.x, h = b >> 2, j = b & 3, rank = b & 1, pair = b >> 1;
    const uint32_t bars = sb + S_BAR;
    unsigned char* const sp = p.s;
    const uint32_t t_start = clk32();

    if (warp == 11) {
        float d[4] = {0.f, 0.f, 0.f, 0.f};
        const uint32_t zz = t_start & 0x00010001u, z[4] = {zz, zz, zz, zz};
        mma16816(d, z, zz, zz);
        bar_sync(1, NTHR - 64);
        uint32_t done = 0;
#pragma unroll 1
        for (int i = 0; i < 4096 && done < 2; i++) {
            mma16816(d, z, zz, zz);
            __nanosleep(200);
            done += mbar_mask4(bars + B_F * 8) & 1;
        }
        if (d[0] == 1.f) sts1f(sb + S_EP + 12, d[1]);
        return;
    }
    if (warp == 8) {
        TS(30);
        if (lane == 0) {
            mbar_init(bars, 1);
            asm volatile("fence.mbarrier_init.release.cluster;" ::: "memory");
            mbar_expect_tx(bars, 8192);
            tma4(sb + S_MOD1, &p.m[0], (b >> 1) * 16, (b & 1) * 256, 0, 0, bars, POL_FIRST);
            TS(28);
#pragma unroll
            for (int i = 1; i < NBAR; i++) mbar_init(bars + i * 8, i == B_UK ? 8 : i == B_O ? 4 : 1);
            asm volatile("fence.mbarrier_init.release.cluster;" ::: "memory");
            mbar_expect_tx(bars + B_X * 8, 8192); mbar_expect_tx(bars + (B_X + 1) * 8, 8192);
        }
        __syncwarp();
        TS(27);
        bar_arrive(1, NTHR - 64);
        {
            const int c = lane + 1;
            int mi = 1, k = c - C_WQ, c0 = 0, c1 = j * 128, d1 = 32, c2 = h * 2, c3 = 0, dst = S_WQ;
            if (c >= C_WUK)  { mi = 2; k = c - C_WUK; dst = S_WUK; }
            if (c >= C_CKV)  { mi = 3; k = c - C_CKV; dst = S_CKV; c1 = pair * 128 + (k >> 2) * 64; d1 = 0; c2 = rank * 4 + (k & 3); }
            if (c >= C_T1)   { const int x = (c - C_T1) & 1; k = (c - C_T1) >> 1; dst = x ? S_XCH : S_CKV + 6 * 8192; c1 = pair * 128 + 64; c2 = (rank ^ x) * 4 + 2 + k; }
            if (c >= C_WUV)  { mi = 4; k = c - C_WUV; dst = S_WUV; c1 = j * 16; c2 = k * 2; c3 = h * 2; }
            if (c >= C_WUV + 4) { mi = 5; k = c - C_WO; dst = S_WO; c0 = (b & 15) * 32; c1 = (b >> 4) * 512; d1 = 128; c2 = 0; c3 = 0; }
            if (c == C_MOD2 || c == C_MOD2 + 1) { mi = 8; k = c - C_MOD2; dst = S_MOD2; c0 = 1024 + (b & 63) * 32; c1 = (b >> 6) * 256; }
            if (c >= C_W1)   { mi = 6; k = c - C_W1; dst = S_W1; c0 = b * 16; c1 = 0; d1 = 256; }
            if (c >= C_W2)   { mi = 7; k = c - C_W2; dst = S_W2; c0 = 0; c1 = b * 32; d1 = 16; }
            const uint32_t wa = (uint32_t)c0 | (uint32_t)(c1 + k * d1) << 16;
            const bool keep = c >= C_T1 && c < C_WUV;
            const uint32_t wb = (uint32_t)c2 | (uint32_t)c3 << 8 | (uint32_t)mi << 14 | (uint32_t)keep << 18 | (uint32_t)((dst >> 13) + k) << 24;
            const int nch = b < NFFN ? NCHUNK : C_W1;
#pragma unroll 1
            for (int i = 1; i < nch; i++) {
                const uint32_t ua = __shfl_sync(~0u, wa, i - 1), ub = __shfl_sync(~0u, wb, i - 1);
                if (i == C_T1 + 1) mbar_wait(bars + B_UK * 8);
                if (i == C_W1) mbar_wait(bars + B_QK * 8);
                if (i >= WIN) mbar_wait(bars + (i - WIN) * 8);
                wait_until(t_start, p.sched[i]);
                if (lane == 0) {
                    mbar_expect_tx(bars + i * 8, 8192);
                    tma4(sb + (ub >> 24) * 8192, &p.m[(ub >> 14) & 15], ua & 0xffff, ua >> 16, ub & 0xff, (ub >> 8) & 0x3f, bars + i * 8,
                         (ub >> 18 & 1) ? POL_NORMAL : POL_FIRST);
                }
            }
        }
        TS(20);
        return;
    }
    if (warp == 9) {
        const int col = (lane & 1) * 4 + (lane & 2) + ((lane >> 2) & 1);
        const float be = __bfloat162float(p.b2[(b & 63) * 8 + col]);
        const uint32_t pr0 = G_PROBE + b * 32;
        if (lane < 4) str4(sp + pr0 + (lane & 2) * 2048 + (lane & 1) * 16, 0, 0, 0, 0);
        __syncwarp();
        uint32_t beta = 0;
        if (lane == 0) { beta = probe_near(sp, pr0, sb + S_EP + 12); sts1(sb + S_EP + 4, beta); }
        __syncwarp();
        bar_sync(8, 64);
        if (lane == 0) mbar_arrive(bars + B_BETA * 8);
        TS(69);
        const uint32_t ep = lds1(sb + S_EP);
        const uint32_t tg = ~ep & 1u;
        beta = __shfl_sync(~0u, beta, 0);
        const unsigned char* sg = sp + pick(G_MOD2 + spread((lane & 8) * 1024 + 6144 + (b & 63) * 32 + col * 4), beta);
        const unsigned char* s7 = sp + pick(G_H7 + (b & 63) * 8192 + lane * 16, beta);
        const unsigned char* s7c = s7 + (lane < 2 * (NFFN - 80) ? 2560 : 0);
        mod2_tile(sb, sp, bars, b, 0, lane, tg);
        TS(29);
        if (b >= 64) return;
        mbar_wait(bars + B_F * 8);
        uint32_t w; int it = 0;
#pragma unroll 1
        do { w = ldr1(sg); SPIN_CHECK(it); } while (__any_sync(~0u, (w ^ tg) & 1));
        const float gb = u2f(w) + __shfl_xor_sync(~0u, u2f(w), 8);
        bar_sync(10, 320);
        const uint32_t t_6 = clk32();
        const float x2 = fmaf(gb, be, lds1f(sb + S_X2 + col * 4));
        TS(21);
        wait_until(t_6, p.tm[D_H7]);
        uint4 y[6];
#pragma unroll 1
        do {
#pragma unroll
            for (int i = 0; i < 5; i++) y[i] = ldr4(s7 + i * 512);
            y[5] = ldr4(s7c);
            SPIN_CHECK(it);
        } while (__any_sync(~0u, or3(or3(bad4(y[0], tg), bad4(y[1], tg), bad4(y[2], tg)), or3(bad4(y[3], tg), bad4(y[4], tg), bad4(y[5], tg)), 0) & 1));
        if (lane >= 2 * (NFFN - 80)) y[5] = make_uint4(0, 0, 0, 0);
        const float s0 = ((u2f(y[0].x) + u2f(y[1].x)) + (u2f(y[2].x) + u2f(y[3].x))) + (u2f(y[4].x) + u2f(y[5].x));
        const float s1 = ((u2f(y[0].y) + u2f(y[1].y)) + (u2f(y[2].y) + u2f(y[3].y))) + (u2f(y[4].y) + u2f(y[5].y));
        const float s2 = ((u2f(y[0].z) + u2f(y[1].z)) + (u2f(y[2].z) + u2f(y[3].z))) + (u2f(y[4].z) + u2f(y[5].z));
        const float s3 = ((u2f(y[0].w) + u2f(y[1].w)) + (u2f(y[2].w) + u2f(y[3].w))) + (u2f(y[4].w) + u2f(y[5].w));
        {
            const bool b1 = lane & 2, b2 = lane & 4;
            const float k0 = (b1 ? s2 : s0) + __shfl_xor_sync(~0u, b1 ? s0 : s2, 2), k1 = (b1 ? s3 : s1) + __shfl_xor_sync(~0u, b1 ? s1 : s3, 2);
            float k = (b2 ? k1 : k0) + __shfl_xor_sync(~0u, b2 ? k0 : k1, 4);
            k += __shfl_xor_sync(~0u, k, 8); k += __shfl_xor_sync(~0u, k, 16);
            if (lane < 8) p.out[b * 8 + col] = __float2bfloat16(fmaf(gb, k, x2));
            if (b == 0 && lane == 8) str1(sp + G_EPOCH, ep + 1);
        }
        TS(22);
        return;
    }

    if (warp == 10) {
        const float b1v = __bfloat162float(p.b1[(b < NFFN ? b * 16 : 0) + (lane & 15)]);
        const uint32_t pr4 = G_H4 + pair * 131072 + 65536 + rank * 256;
        const uint32_t prev = ldr1(sp + pr4 + 128);
        if (lane < 4) str4(sp + pr4 + (lane & 2) * 2048 + (lane & 1) * 16, 0, 0, 0, 0);
        __syncwarp();
        uint32_t beta4 = 0;
        if (lane == 0) beta4 = probe_near(sp, pr4, sb + S_X2);
        beta4 = __shfl_sync(~0u, beta4, 0);
        bar_sync(11, 64);
        const uint32_t tg = ~lds1(sb + S_EP) & 1u;
        {
            const uint32_t held = (prev & 24) ^ (8u << beta4), t4 = held >> (3 + beta4) & 1;
            const uint32_t w = tg | beta4 << 1 | t4 << 2 | held;
            if (lane < 2) str4(sp + pr4 + 128 + lane * 16, w, w, w, w);
            if (lane == 0) sts1(sb + S_EP + 8, w);
#pragma unroll 1
            for (int i = 0; i < 32; i++) {
                wait_until(t_start, WARM_T0 + i * WARM);
                str4(sp + pick(G_H4 + pair * 131072 + spread((i * 4 + (lane >> 3)) * 256 + rank * 128 + (lane & 7) * 16), beta4), t4 ^ 1, 0, t4 ^ 1, 0);
            }
            __syncwarp();
            if (lane == 0) mbar_arrive(bars + B_BETA4 * 8);
        }
        TS(70);
        mbar_wait(bars + B_BETA * 8);
        const uint32_t beta = lds1(sb + S_EP + 4);
        const unsigned char* sm_a = sp + pick(G_ML + spread(lane * 256 + h * 4), beta);
        const unsigned char* sm_b = sp + pick(G_ML + spread((lane + 32) * 256 + h * 4), beta);
        mbar_wait(bars + B_O * 8);
        wait_until(clk32() - p.tm[A_H4] - 40, p.tm[D_H4]);
        wait_until(t_start, p.tm[T_H4] - p.tm[A_H4] - 40);
        uint32_t ma, mb, la, lb; int it = 0;
        TS(76);
#pragma unroll 1
        do {
            ma = ldr1(sm_a); mb = ldr1(sm_b); la = ldr1(sm_a + 128); lb = ldr1(sm_b + 128);
            SPIN_CHECK(it);
        } while (__any_sync(~0u, (xo2(ma, mb, tg) | xo2(la, lb, tg)) & 1));
        TS(77);
        const float M = u2f(ordf(__reduce_max_sync(~0u, max((int)ordf(ma), (int)ordf(mb)))));
        const float wa = ex2(u2f(ma) - M), wb = ex2(u2f(mb) - M);
        const float L = __fdividef(262144.f, __uint2float_rn(__reduce_add_sync(~0u, __float2uint_rn(fmaf(wa, u2f(la), wb * u2f(lb)) * 262144.f))));
        sts1f(sb + S_ML + lane * 4, wa * L); sts1f(sb + S_ML + 128 + lane * 4, wb * L);
        __syncwarp();
        if (lane == 0) mbar_arrive(bars + B_W * 8);
        TS(78);
        mod2_tile(sb, sp, bars, b, 1, lane, tg);
        if (b < NFFN) {
            const uint32_t a = sb + S_RED + (lane & 15) * 32 + (lane >> 4) * 16;
            const uint32_t as = sb + S_RED + 1536 + (lane >> 4) * 16;
            bar_sync(9, 288);
            const float4 sa = lds4f(as + 8 * 32), ta = lds4f(as + 6 * 32), tc = lds4f(as + 7 * 32);
            const float4 U = lds4f(a), G = lds4f(a + 512), S = lds4f(a + 1024);
            float mu = (sa.x + sa.y) + (sa.z + sa.w), ex = ((ta.x + ta.y) + (ta.z + ta.w)) + ((tc.x + tc.y) + (tc.z + tc.w));
            float us = (U.x + U.y) + (U.z + U.w), gs = (G.x + G.y) + (G.z + G.w), ss = (S.x + S.y) + (S.z + S.w);
            mu += __shfl_xor_sync(~0u, mu, 16); ex += __shfl_xor_sync(~0u, ex, 16);
            us += __shfl_xor_sync(~0u, us, 16); gs += __shfl_xor_sync(~0u, gs, 16); ss += __shfl_xor_sync(~0u, ss, 16);
            mu *= 1.f / 512.f;
            float rstd;
            asm("rsqrt.approx.ftz.f32 %0, %1;" : "=f"(rstd) : "f"(fmaxf(fmaf(ex, 1.f / 512.f, -mu * mu), 0.f) + 1e-5f));
            const float pre = (us - mu * gs) * rstd + (ss + b1v);
            const float z = pre * fmaf(pre * pre, 0.044715f * 2.302208198f, 2.302208198f);
            sts1f(sb + S_STAT + (lane & 15) * 4, __fdividef(pre, 1.f + ex2(fminf(-z, 126.f))));
            bar_arrive(10, b < 64 ? 320 : 288);
        }
        return;
    }

    const int g = lane >> 2, q = lane & 3;
    const int wg = warp >> 2, wq = warp & 3;
    const uint32_t ep0 = ldr1(sp + G_EPOCH);
    const uint32_t tg = ~ep0 & 1u;
    const uint32_t cw = *reinterpret_cast<const uint32_t*>(p.c + tid * 2);
    const uint4 xa = *reinterpret_cast<const uint4*>(p.x + lane * 16), xb = *reinterpret_cast<const uint4*>(p.x + lane * 16 + 8);
    const uint32_t xw2 = *reinterpret_cast<const uint32_t*>(p.x + tid * 2);
    const float xm = __bfloat162float(p.x[j * 128 + (tid & 127)]);
    {
        uint32_t z = ~0u, zv = tg ^ 1u;
        if (tid < 4) z = G_H1 + spread((b & 1) * 4096 + (b >> 1) * 64 + tid * 16);
        else if (tid >= 8 && tid < 16) z = G_MOD2 + spread(b * 128 + (tid & 7) * 16);
        else if (tid >= 112 && tid < 120) z = G_H6 + spread(b * 128 + (tid & 7) * 16);
        else if (tid >= 16 && tid < 32) { const uint32_t o = G_ML + spread(pair * 256 + (tid & 15) * 16) + rank * 4096; str4(sp + o, zv, zv, zv, zv); }
        else if (tid >= 32 && tid < 64) z = G_H2 + spread(b * 512 + lane * 16);
        else if (tid >= 64 && tid < 96) z = G_H5 + spread(b * 512 + lane * 16);
        else if (tid >= 96 && tid < 112) { z = G_H3 + spread((j * 2 + ((tid >> 3) & 1)) * 4096 + h * 128 + (tid & 7) * 16); zv = 0; }
        if (z != ~0u) { str4(sp + z, zv, zv, zv, zv); str4(sp + z + 4096, zv, zv, zv, zv); }
    }
    if (tid == 0) sts1(sb + S_EP, ep0);
    if (tid < 64) sts1(sb + S_MAX + tid * 4, 0x80000000u);
    sts1(sb + S_ONES + tid * 4, 0x3F803F80u);
    {
        const float c0 = bflo(cw), c1 = bfhi(cw);
        const float s0 = __fdividef(c0, 1.f + __expf(fminf(-c0, 80.f))), s1 = __fdividef(c1, 1.f + __expf(fminf(-c1, 80.f)));
        uint32_t hi, lo; split2(s0, s1, hi, lo);
        const uint32_t a = sb + S_SC + (tid >> 4) * 128 + vpos((tid & 15) * 2);
        sts1(a, hi); sts1(a + 64, lo);
    }
    TS0(0);
    bar_sync(1, NTHR - 64);
    if (warp == 7) bar_arrive(8, 64); else if (warp == 6) bar_arrive(11, 64);

    const uint32_t vlane = (g & 1) * 64 + q * 16;

    {
        float d0[4] = {0.f, 0.f, 0.f, 0.f}, d1[4] = {0.f, 0.f, 0.f, 0.f};
        mbar_wait(bars + C_MOD1 * 8);
        step32(sb + S_MOD1 + warp * 1024, sb + S_SC + ((b & 1) * 8 + warp) * 128 + vlane, lane, d0, d1);
        reduce16_publish(sb, d0, d1, tid, warp, lane, sp + G_H1 + spread((b & 1) * 4096 + (b >> 1) * 64), tg);
    }
    TS0(1);
    float mean1, rstd1;
    {
        const uint32_t w[8] = {xa.x, xa.y, xa.z, xa.w, xb.x, xb.y, xb.z, xb.w};
        float s = 0.f;
#pragma unroll
        for (int i = 0; i < 8; i++) s += bflo(w[i]) + bfhi(w[i]);
#pragma unroll
        for (int o = 16; o; o >>= 1) s += __shfl_xor_sync(~0u, s, o);
        mean1 = s * (1.f / 512.f);
        float v = 0.f;
#pragma unroll
        for (int i = 0; i < 8; i++) { float a = bflo(w[i]) - mean1, c = bfhi(w[i]) - mean1; v += a * a + c * c; }
#pragma unroll
        for (int o = 16; o; o >>= 1) v += __shfl_xor_sync(~0u, v, o);
        rstd1 = rsqrtf(v * (1.f / 512.f) + 1e-5f);
    }
    if (tid < 128) {
        const unsigned char* s0 = sp + G_H1 + j * 512 + tid * 4;
        const unsigned char* s1 = s0 + 8192;
        uint4 a; int it = 0;
        wait_until(t_start, p.tm[T_H1]);
#pragma unroll 1
        do {
            a.x = ldr1(s0); a.y = ldr1(s1); a.z = ldr1(s0 + 2048); a.w = ldr1(s1 + 2048);
            SPIN_CHECK(it);
        } while (bad4(a, tg) & 1);
        const float hv = (xm - mean1) * rstd1 * (1.f + (u2f(a.z) + u2f(a.w))) + (u2f(a.x) + u2f(a.y));
        uint32_t hi, lo; split2(hv, 0.f, hi, lo);
        const uint32_t ad = sb + S_VEC + (tid >> 5) * 128 + vpos(tid & 31);
        stsh(ad, hi); stsh(ad + 64, lo);
    }
    TS0(2);
    bar_sync(2, 256);
    {
        float r0, r1;
        gemv128<true>(sb + S_WQ, sb + S_VEC, bars + C_WQ * 8, warp, lane, r0, r1);
        const float t0 = __shfl_sync(~0u, r0, lane & 28), t1 = __shfl_sync(~0u, r1, lane & 28);
        str1(sp + G_H2 + spread(b * 512 + warp * 64 + (q & 1) * 32 + g * 4) + (q >> 1) * 4096, tagf((q & 1) ? t1 : t0, tg));
    }
    TS0(3);
    mbar_wait(bars + B_BETA * 8);
    const uint32_t beta = lds1(sb + S_EP + 4);
    bar_sync(2, 256);
    if (tid < 128) {
        const unsigned char* src = sp + pick(G_H2 + spread(h * 2048 + tid * 4), beta);
        uint4 a; int it = 0;
#pragma unroll 1
        do {
            a.x = ldr1(src); a.y = ldr1(src + 512); a.z = ldr1(src + 1024); a.w = ldr1(src + 1536);
            SPIN_CHECK(it);
        } while (bad4(a, tg) & 1);
        const float qv = ((u2f(a.x) + u2f(a.y)) + (u2f(a.z) + u2f(a.w))) * (0.08838834764831845f * 1.4426950408889634f);
        uint32_t hi, lo; split2(qv, 0.f, hi, lo);
        const uint32_t ad = sb + S_VEC + (tid >> 5) * 128 + vpos(tid & 31);
        stsh(ad, hi); stsh(ad + 64, lo);
    }
    TS0(4);
    bar_sync(2, 256);
    {
        float r0, r1;
        gemv128<false>(sb + S_WUK, sb + S_VEC, bars + C_WUK * 8, warp, lane, r0, r1);
        const float n0 = __shfl_down_sync(~0u, r0, 4), m0 = __shfl_up_sync(~0u, r1, 4);
        const uint32_t w = (g & 1) ? packbf(m0, r1) : packbf(r0, n0);
        const uint32_t w2 = __shfl_sync(~0u, w, lane & 28);
        if (q < 2) {
            const int chunk = ((warp & 3) * 2 + (g & 1)) ^ (h & 7);
            str1(sp + G_H3 + (j * 2 + (warp >> 2)) * 8192 + q * 4096 + h * 128 + chunk * 16 + (g >> 1) * 4, w2 ^ 0xFFFF0000u);
        }
        if (lane == 0) mbar_arrive(bars + B_UK * 8);
    }
    TS0(5);
    {
        const unsigned char* src[6];
#pragma unroll
        for (int i = 0; i < 6; i++) src[i] = sp + pick(G_H3 + (i < 4 ? rank * 4 + i : (rank ^ 1) * 4 + i - 2) * 8192 + tid * 16, beta);
        uint4 v[6];
        wait_until(t_start, p.tm[T_H3]);
#pragma unroll
        for (int i = 0; i < 6; i++) v[i] = ldr4(src[i]);
        int it = 0;
#pragma unroll 1
        while (true) {
            bool ok = true;
#pragma unroll
            for (int i = 0; i < 6; i++) if (!nz4(v[i])) { v[i] = ldr4(src[i]); ok = false; }
            if (__all_sync(~0u, ok)) break;
            SPIN_CHECK(it);
        }
        TS0(31);
#pragma unroll
        for (int i = 0; i < 6; i++)
            sts4(sb + S_QABS + i * 4096 + tid * 16, v[i].x ^ 0xFFFF0000u, v[i].y ^ 0xFFFF0000u, v[i].z ^ 0xFFFF0000u, v[i].w ^ 0xFFFF0000u);
        fence_async();
        bar_sync(2, 256);
    }
    TS0(6);
    if (wg) {
        uint32_t bw; int it = 0;
#pragma unroll 1
        do { bw = ldr1(sp + G_H4 + 65536 + 128 + ((tid & 127) >> 1) * 131072 + (tid & 1) * 256); SPIN_CHECK(it); } while (__any_sync(~0u, (bw ^ tg) & 1));
        const uint32_t mb = __ballot_sync(~0u, bw & 2), mt = __ballot_sync(~0u, bw & 4);
        if (lane == 0) sts2(sb + S_B4 + wq * 8, mb, mt);
    }
    if (b < NFFN) {
        unsigned char* d7 = sp + G_H7 + (tid >> 2) * 8192 + b * 32 + (tid & 3) * 8;
        str2(d7, tg ^ 1, tg ^ 1); str2(d7 + 4096, tg ^ 1, tg ^ 1);
    }
    {
        float s[16];
#pragma unroll
        for (int i = 0; i < 16; i++) s[i] = 0.f;
        const uint32_t xo = (wg ? S_XBUF1 : S_XBUF0) + (tid & 127) * 16;
#pragma unroll 1
        for (int cg = 0; cg < 4 - 2 * wg; cg++) {
            mbar_wait(bars + (C_CKV + wg * 4 + cg) * 8);
            const uint64_t da = mkdesc(sb + S_CKV + (wg * 4 + cg) * 8192), db = mkdesc(sb + S_QABS + cg * 4096);
            wg_fence();
#pragma unroll
            for (int k = 0; k < 4; k++) wgmma_n32<0>(s, da + k * 2, db + k * 2, 1);
            wg_commit();
        }
        wg_wait<0>();
        reg_fence16(s);
        TS0(64);
        {
            uint32_t ra, rb;
            asm("mapa.shared::cluster.u32 %0, %1, %2;" : "=r"(ra) : "r"(sb + xo), "r"(rank ^ 1));
            asm("mapa.shared::cluster.u32 %0, %1, %2;" : "=r"(rb) : "r"(bars + (B_X + wg) * 8), "r"(rank ^ 1));
#pragma unroll
            for (int i = 0; i < 4; i++)
                asm volatile("st.async.weak.shared::cluster.mbarrier::complete_tx::bytes.v4.f32 [%0], {%1,%2,%3,%4}, [%5];"
                             ::"r"(ra + i * 2048), "f"(s[4 * i]), "f"(s[4 * i + 1]), "f"(s[4 * i + 2]), "f"(s[4 * i + 3]), "r"(rb) : "memory");
        }
        float4 xs[4];
#define QK_TAIL(c) do { \
            mbar_wait2(bars + (C_T1 + 2 * (c)) * 8); \
            const uint64_t da = mkdesc(sb + S_CKV + (6 + (c)) * 8192), dx = mkdesc(sb + S_XCH + (c) * 8192), db = mkdesc(sb + S_QABS + (2 + (c)) * 4096); \
            wg_fence(); \
            _Pragma("unroll") for (int k = 0; k < 4; k++) { wgmma_n32<0>(s, da + k * 2, db + k * 2, 1); wgmma_n32<0>(s, dx + k * 2, db + 512 + k * 2, 1); } \
            wg_commit(); } while (0)
        if (wg) QK_TAIL(0);
        mbar_wait_cluster(bars + (B_X + wg) * 8);
#pragma unroll
        for (int i = 0; i < 4; i++) xs[i] = lds4f(sb + xo + i * 2048);
        if (wg) QK_TAIL(1);
        wg_wait<0>();
        reg_fence16(s);
        TS4(7); TS0(65);
#pragma unroll
        for (int i = 0; i < 4; i++) { s[4 * i] += xs[i].x; s[4 * i + 1] += xs[i].y; s[4 * i + 2] += xs[i].z; s[4 * i + 3] += xs[i].w; }
        const bool b2 = lane & 16, b1 = lane & 8, b0 = lane & 4;
        {
            float v[8];
#pragma unroll
            for (int i = 0; i < 4; i++) { v[2 * i] = fmaxf(s[4 * i], s[4 * i + 2]); v[2 * i + 1] = fmaxf(s[4 * i + 1], s[4 * i + 3]); }
            float u[4];
#pragma unroll
            for (int k = 0; k < 4; k++) u[k] = fmaxf(b2 ? v[k + 4] : v[k], __shfl_xor_sync(~0u, b2 ? v[k] : v[k + 4], 16));
            float t[2];
#pragma unroll
            for (int k = 0; k < 2; k++) t[k] = fmaxf(b1 ? u[k + 2] : u[k], __shfl_xor_sync(~0u, b1 ? u[k] : u[k + 2], 8));
            const uint32_t r = ordf(__float_as_uint(fmaxf(b0 ? t[1] : t[0], __shfl_xor_sync(~0u, b0 ? t[0] : t[1], 4))));
            const uint32_t a = sb + S_MAX + (8 * (g >> 1) + 2 * q + (g & 1)) * 4;
            red_max(a + 128, r);
            if (wg == 0) red_max(a, r);
        }
        if (wg == 0) { bar_arrive(4, 256); bar_sync(3, 128); } else { bar_arrive(7, 256); bar_sync(4, 256); }
        TS4(66);
        uint32_t pk[8];
#pragma unroll
        for (int i = 0; i < 4; i++) {
            const float2 mm = lds2f(sb + S_MAX + wg * 128 + (8 * i + 2 * q) * 4);
            const float m0 = u2f(ordf(__float_as_uint(mm.x))), m1 = u2f(ordf(__float_as_uint(mm.y)));
            pk[2 * i] = packbf(ex2(s[4 * i] - m0), ex2(s[4 * i + 1] - m1));
            pk[2 * i + 1] = packbf(ex2(s[4 * i + 2] - m0), ex2(s[4 * i + 3] - m1));
        }
        {
            const int t = lane >> 3, r8 = lane & 7;
            const uint32_t a = sb + S_P + wg * 4096 + ((t >> 1) * 8 + r8) * 128 + (((2 * wq + (t & 1)) ^ r8) << 4);
            stsm4t(a, pk[0], pk[1], pk[2], pk[3]);
            stsm4t(a + 2048, pk[4], pk[5], pk[6], pk[7]);
        }
        fence_async();
        TS4(67); TS0(68);
        if (wg) {
            bar_arrive(5, 256);
            if (warp == 4) {
                str1(sp + G_ML + spread(pair * 256 + lane * 4) + rank * 4096, tagf(u2f(ordf(lds1(sb + S_MAX + 128 + lane * 4))), tg));
                if (lane == 0) mbar_arrive(bars + B_QK * 8);
            }
        } else {
            float o0[16], o1[16], o2[16], o3[16], ol[16];
            const uint64_t d1 = mkdesc(sb + S_ONES) & ~(0x3FFFull << 32);
            const uint64_t db = mkdesc(sb + S_P), da = mkdesc(sb + S_CKV);
            bar_sync(3, 128);
            wg_fence();
#pragma unroll
            for (int k = 0; k < 4; k++) {
                wgmma_n32<1>(o0, da + k * 128, db + k * 2, k);
                wgmma_n32<1>(o1, da + 512 + k * 128, db + k * 2, k);
                wgmma_n32<1>(o2, da + 1024 + k * 128, db + k * 2, k);
                wgmma_n32<1>(o3, da + 1536 + k * 128, db + k * 2, k);
                wgmma_n32<0>(ol, d1, db + k * 2, k);
            }
            wg_commit();
            wg_wait<0>();
            reg_fence16(o0); reg_fence16(o1); reg_fence16(o2); reg_fence16(o3); reg_fence16(ol);
            TS0(23);
            bar_sync(7, 256);
            {
                const float al = ex2(u2f(ordf(lds1(sb + S_MAX + lane * 4))) - u2f(ordf(lds1(sb + S_MAX + 128 + lane * 4))));
#pragma unroll
                for (int i = 0; i < 4; i++) {
                    const float a0 = __shfl_sync(~0u, al, 8 * i + 2 * q), a1 = __shfl_sync(~0u, al, 8 * i + 2 * q + 1);
                    o0[4 * i] *= a0; o0[4 * i + 1] *= a1; o0[4 * i + 2] *= a0; o0[4 * i + 3] *= a1;
                    o1[4 * i] *= a0; o1[4 * i + 1] *= a1; o1[4 * i + 2] *= a0; o1[4 * i + 3] *= a1;
                    o2[4 * i] *= a0; o2[4 * i + 1] *= a1; o2[4 * i + 2] *= a0; o2[4 * i + 3] *= a1;
                    o3[4 * i] *= a0; o3[4 * i + 1] *= a1; o3[4 * i + 2] *= a0; o3[4 * i + 3] *= a1;
                    ol[4 * i] *= a0; ol[4 * i + 1] *= a1; ol[4 * i + 2] *= a0; ol[4 * i + 3] *= a1;
                }
            }
            mbar_wait(bars + B_BETA4 * 8);
            const uint32_t rec = lds1(sb + S_EP + 8), tg4w = rec >> 2 & 1;
            unsigned char* const h4dst = sp + pick(G_H4 + pair * 131072 + spread(q * 2048 + wq * 256 + rank * 128 + g * 8), rec >> 1);
            unsigned char* ldst = sp + G_ML + spread(pair * 256 + 128 + wq * 32 + q * 8) + rank * 4096;
            PIN(ldst);
            TS0(81);
            bar_sync(5, 256);
            wg_fence();
#pragma unroll
            for (int k = 0; k < 4; k++) {
                wgmma_n32<1>(o0, da + 2048 + k * 128, db + 256 + k * 2, 1);
                wgmma_n32<1>(o1, da + 2048 + 512 + k * 128, db + 256 + k * 2, 1);
            }
            wg_commit();
            wg_wait<0>();
            reg_fence16(o0); reg_fence16(o1);
            TS0(24);
            wg_fence();
#pragma unroll
            for (int k = 0; k < 4; k++) wgmma_n32<1>(o2, da + 2048 + 1024 + k * 128, db + 256 + k * 2, 1);
            wg_commit();
#define O_STORE(A, B, OFF) _Pragma("unroll") for (int i = 0; i < 4; i++) _Pragma("unroll") for (int e = 0; e < 2; e++) { \
                const float f0 = u2f((__float_as_uint(A[4 * i + e]) + 0x10000u) & 0xFFFE0000u); \
                str64(h4dst + (OFF) + i * 16384 + e * 1024, packbf(f0, A[4 * i + 2 + e]) | tg4w, packbf(B[4 * i + e], B[4 * i + 2 + e])); }
            TS0(8);
            O_STORE(o0, o1, 0);
            __syncwarp();
            wg_fence();
#pragma unroll
            for (int k = 0; k < 4; k++) {
                wgmma_n32<1>(o3, da + 2048 + 1536 + k * 128, db + 256 + k * 2, 1);
                wgmma_n32<0>(ol, d1, db + 256 + k * 2, 1);
            }
            wg_commit();
            wg_wait<0>();
            reg_fence16(o2); reg_fence16(o3); reg_fence16(ol);
            {
                const float l0 = (wq & 2) ? ((wq & 1) ? ol[12] : ol[8]) : ((wq & 1) ? ol[4] : ol[0]);
                const float l1 = (wq & 2) ? ((wq & 1) ? ol[13] : ol[9]) : ((wq & 1) ? ol[5] : ol[1]);
                if (g == 0) str2(ldst, tagf(l0, tg), tagf(l1, tg));
            }
            O_STORE(o2, o3, 64);
            if (lane == 0) mbar_arrive(bars + B_O * 8);
        }
    }
    TS0(9);
    const uint32_t t_o = clk32();
    uint32_t af[8][4];
    {
        const int sg = wq * 4 + (lane >> 3), ur = (lane >> 2) & 1;
        const int po = ur * 128 + (wg ^ 1) * 64 + q * 16;
        uint32_t a0;
        {
            const int m = lane >> 3, r8 = lane & 7;
            const int row = (m >> 1) * 16 + (r8 >> 1) * 2 + (r8 & 1) * 8;
            a0 = sb + S_WUV + wg * 4096 + row * 128 + (((wq * 2 + (m & 1)) ^ (row & 7)) << 4);
        }
        const unsigned char* src[4];
        uint32_t tg4[4];
#pragma unroll
        for (int i = 0; i < 4; i++) {
            const float2 m = lds2f(sb + S_B4 + i * 8);
            src[i] = sp + pick(G_H4 + (sg + 16 * i) * 131072 + spread(b * 256 + po), __float_as_uint(m.x) >> (sg * 2 + ur));
            tg4[i] = __float_as_uint(m.y) >> (sg * 2 + ur);
        }
        uint4 v[4];
        uint32_t have = 0;
        int it = 0;
        unsigned char* d5 = sp + G_H5 + spread(b * 512 + warp * 64 + (q & 1) * 32 + g * 4) + (q >> 1) * 4096;
        PIN(d5);
        if (wg) mbar_wait(bars + B_O * 8);
        wait_until(wg ? clk32() - p.tm[A_H4] : t_o, p.tm[D_H4]);
        wait_until(t_start, p.tm[T_H4] - (wg ? p.tm[A_H4] : 0));
#pragma unroll
        for (int i = 0; i < 4; i++) v[i] = ldr64x2(src[i]);
        TS0(10);
#define LOAD_UV(now) _Pragma("unroll") for (int i = 0; i < 4; i++) \
            if ((now) >> i & 1) { ldsm4t(a0 + i * 8192, af[2 * i]); ldsm4t((a0 + i * 8192 + 128) ^ 16, af[2 * i + 1]); }
        have = mbar_mask4(bars + C_WUV * 8);
        LOAD_UV(have);
        mbar_wait(bars + B_W * 8);
        float wt[4];
#pragma unroll
        for (int i = 0; i < 4; i++) wt[i] = lds1f(sb + S_ML + (sg + 16 * i) * 4);
#pragma unroll 1
        while (__any_sync(~0u, (or3(xo2(v[0].x, v[0].z, tg4[0]), xo2(v[1].x, v[1].z, tg4[1]), xo2(v[2].x, v[2].z, tg4[2])) | xo2(v[3].x, v[3].z, tg4[3])) & 1)) {
#pragma unroll
            for (int i = 0; i < 4; i++) if (xo2(v[i].x, v[i].z, tg4[i]) & 1) v[i] = ldr64x2(src[i]);
            SPIN_CHECK(it);
        }
        float acc[8] = {0.f, 0.f, 0.f, 0.f, 0.f, 0.f, 0.f, 0.f};
#pragma unroll
        for (int i = 0; i < 4; i++) {
            const uint32_t w[4] = {v[i].x & ~1u, v[i].y, v[i].z & ~1u, v[i].w};
#pragma unroll
            for (int k = 0; k < 4; k++) {
                acc[2 * k] = fmaf(wt[i], bflo(w[k]), acc[2 * k]);
                acc[2 * k + 1] = fmaf(wt[i], bfhi(w[k]), acc[2 * k + 1]);
            }
        }
        TS0(25);
        {
            const bool u16 = lane & 16, u8 = lane & 8;
            float r[4];
#pragma unroll
            for (int k = 0; k < 4; k++) r[k] = (u16 ? acc[k + 4] : acc[k]) + __shfl_xor_sync(~0u, u16 ? acc[k] : acc[k + 4], 16);
            const float t0 = (u8 ? r[2] : r[0]) + __shfl_xor_sync(~0u, u8 ? r[0] : r[2], 8);
            const float t1 = (u8 ? r[3] : r[1]) + __shfl_xor_sync(~0u, u8 ? r[1] : r[3], 8);
            uint32_t hi, lo; split2(t0, t1, hi, lo);
            const uint32_t a = sb + S_RED + wq * 320 + po + (u16 ? 8 : 0) + (u8 ? 4 : 0);
            sts1(a, hi); sts1(a + 4 * 320, lo);
        }
        bar_sync(2, 256);
        uint4 bq[4];
#pragma unroll
        for (int i = 0; i < 4; i++) bq[i] = lds4(sb + S_RED + g * 320 + i * 64 + q * 16);
        if (have != 15) { mbar_wait4(bars + C_WUV * 8); LOAD_UV(~have); }
        float d[4][4];
#pragma unroll
        for (int i = 0; i < 4; i++) {
            d[i][0] = d[i][1] = d[i][2] = d[i][3] = 0.f;
            mma16816(d[i], af[2 * i], bq[i].x, bq[i].y);
            mma16816(d[i], af[2 * i + 1], bq[i].z, bq[i].w);
        }
        const float r0 = ((d[0][0] + d[0][1]) + (d[1][0] + d[1][1])) + ((d[2][0] + d[2][1]) + (d[3][0] + d[3][1]));
        const float r1 = ((d[0][2] + d[0][3]) + (d[1][2] + d[1][3])) + ((d[2][2] + d[2][3]) + (d[3][2] + d[3][3]));
        float r = ((q & 1) ? r1 : r0) + __shfl_xor_sync(~0u, (q & 1) ? r0 : r1, 1);
        r += __shfl_xor_sync(~0u, r, 2);
        str1(d5, tagf(r, tg));
    }
    const uint32_t t_e = clk32();
    TS0(12);
    const unsigned char* sm[4];
    uint2 mm[6];
#pragma unroll
    for (int i = 0; i < 4; i++) sm[i] = sp + pick(G_MOD2 + i * 8192 + tid * 8, beta);
#define LOAD_MM() do { mm[0] = ldr2(sm[0]); mm[1] = ldr2(sm[0] + 2048); mm[2] = ldr2(sm[1]); mm[3] = ldr2(sm[2]); mm[4] = ldr2(sm[2] + 2048); mm[5] = ldr2(sm[3]); } while (0)
#define BAD_MM() or3(or3(bad2(mm[0], tg), bad2(mm[1], tg), bad2(mm[2], tg)), or3(bad2(mm[3], tg), bad2(mm[4], tg), bad2(mm[5], tg)), 0)
    {
        const int m = lane >> 3, r8 = lane & 7;
        const uint32_t a0 = sb + S_WO + (warp >> 1) * 2048 + ((m >> 1) * 8 + r8) * 64 + ((((warp & 1) * 2 + (m & 1)) ^ (r8 >> 1)) << 4);
        const unsigned char* src = sp + pick(G_H5 + spread(((b >> 4) * 4 + (warp >> 1)) * 2048 + (tid & 63) * 8), beta);
        uint2 c0, c1, c2, c3; int it = 0;
        uint32_t have = 0;
        unsigned char* d6 = sp + G_H6 + spread(b * 128 + lane * 4) + (warp & 1) * 4096;
        PIN(d6);
        wait_until(t_e, p.tm[D_H5]);
#pragma unroll 1
        do {
            c0 = ldr2(src); c1 = ldr2(src + 512); c2 = ldr2(src + 1024); c3 = ldr2(src + 1536);
            const uint32_t now = mbar_mask4(bars + C_WO * 8) & ~have;
#pragma unroll
            for (int i = 0; i < 4; i++)
                if (now >> i & 1) { ldsm4t(a0 + i * 8192, af[2 * i]); ldsm4t(a0 + i * 8192 + 1024, af[2 * i + 1]); }
            have |= now;
            SPIN_CHECK(it);
        } while (__any_sync(~0u, or3(or3(bad2(c0, tg), bad2(c1, tg), bad2(c2, tg)), bad2(c3, tg), 0) & 1));
        uint32_t hi, lo;
        split2((u2f(c0.x) + u2f(c1.x)) + (u2f(c2.x) + u2f(c3.x)), (u2f(c0.y) + u2f(c1.y)) + (u2f(c2.y) + u2f(c3.y)), hi, lo);
        const uint32_t a = sb + S_FVEC + (tid >> 4) * 128 + vpos((tid & 15) * 2);
        sts1(a, hi); sts1(a + 64, lo);
        TS0(14);
        bar_sync(2, 256);
        if (b < NFFN) LOAD_MM();
        uint4 bq[4];
#pragma unroll
        for (int i = 0; i < 4; i++) bq[i] = lds4(sb + S_FVEC + (i * 4 + (warp >> 1)) * 128 + vlane);
        if (have != 15) {
#pragma unroll
            for (int i = 0; i < 4; i++)
                if (!(have >> i & 1)) {
                    mbar_wait(bars + (C_WO + i) * 8);
                    ldsm4t(a0 + i * 8192, af[2 * i]); ldsm4t(a0 + i * 8192 + 1024, af[2 * i + 1]);
                }
        }
        float d[4][4];
#pragma unroll
        for (int i = 0; i < 4; i++) {
            d[i][0] = d[i][1] = d[i][2] = d[i][3] = 0.f;
            mma16816(d[i], af[2 * i], bq[i].x, bq[i].y);
            mma16816(d[i], af[2 * i + 1], bq[i].z, bq[i].w);
        }
        TS0(15);
        {
            const uint32_t o = sb + (q ? S_RED + tid * 4 : S_R16 + ((warp & 1) * 16 + g) * 16 + (warp >> 1) * 4);
            sts1f(o, ((d[0][0] + d[0][1]) + (d[1][0] + d[1][1])) + ((d[2][0] + d[2][1]) + (d[3][0] + d[3][1])));
            sts1f(o + 128, ((d[0][2] + d[0][3]) + (d[1][2] + d[1][3])) + ((d[2][2] + d[2][3]) + (d[3][2] + d[3][3])));
        }
        bar_sync(2, 256);
        if (tid < 64) {
            const float4 u = lds4f(sb + S_R16 + lane * 16);
            str1(d6, tagf((u.x + u.y) + (u.z + u.w), tg));
        }
        if (tid == 64) mbar_arrive(bars + B_F * 8);
        if (tid >= 224) str4(sp + G_H3 + (j * 2 + ((tid >> 3) & 1)) * 8192 + (tid & 16) * 256 + h * 128 + (tid & 7) * 16, 0, 0, 0, 0);
    }
    const uint32_t t_f = clk32();
    TS0(26);
    if (b < NFFN) {
        const uint32_t ga_ = sb + S_GVEC + (warp * 2 + (lane >> 4)) * 512 + vpos((lane & 15) * 2);
        TS0(16);
        const int m = lane >> 3, r8 = lane & 7;
        const uint32_t a0 = sb + S_W1 + warp * 2048 + ((m >> 1) * 8 + r8) * 32 + (((m & 1) ^ (r8 >> 2)) << 4);
        bool have1 = false;
        unsigned char* d7 = sp + G_H7 + (tid >> 2) * 8192 + b * 32 + (tid & 3) * 8;
        PIN(d7);
        float x20, x21;
        {
            const unsigned char* so[4];
#pragma unroll
            for (int i = 0; i < 4; i++) so[i] = sp + pick(G_H6 + i * 8192 + tid * 8, beta);
            uint2 c[8]; int it = 0;
            float g0, g1;
#define STAGE_MM() do { \
                g0 = 1.f + (u2f(mm[2].x) + u2f(mm[5].x)); g1 = 1.f + (u2f(mm[2].y) + u2f(mm[5].y)); \
                uint32_t hi, lo; \
                split2(g0, g1, hi, lo); sts1(ga_ + 128, hi); sts1(ga_ + 192, lo); \
                split2(u2f(mm[1].x) + u2f(mm[4].x), u2f(mm[1].y) + u2f(mm[4].y), hi, lo); sts1(ga_ + 256, hi); sts1(ga_ + 320, lo); } while (0)
#pragma unroll 1
            while (BAD_MM() & 1) { LOAD_MM(); SPIN_CHECK(it); }
            STAGE_MM();
            have1 = mbar_mask4(bars + C_W1 * 8) >> wg & 1;
            if (have1) {
#pragma unroll
                for (int i = 0; i < 4; i++) ldsm4t(a0 + i * 512, af[i]);
            }
            wait_until(t_f, p.tm[D_H6]);
#pragma unroll 1
            while (true) {
#pragma unroll
                for (int i = 0; i < 8; i++) c[i] = ldr2(so[i >> 1] + (i & 1) * 2048);
                uint32_t bc = 0;
                bc = or3(or3(bad2(c[0], tg), bad2(c[1], tg), bad2(c[2], tg)), or3(bad2(c[3], tg), bad2(c[4], tg), bad2(c[5], tg)),
                         or3(bad2(c[6], tg), bad2(c[7], tg), bc));
                if (!__any_sync(~0u, bc & 1)) break;
                SPIN_CHECK(it);
            }
            x20 = fmaf(u2f(mm[0].x) + u2f(mm[3].x),
                       ((u2f(c[0].x) + u2f(c[1].x)) + (u2f(c[2].x) + u2f(c[3].x))) + ((u2f(c[4].x) + u2f(c[5].x)) + (u2f(c[6].x) + u2f(c[7].x))), bflo(xw2));
            x21 = fmaf(u2f(mm[0].y) + u2f(mm[3].y),
                       ((u2f(c[0].y) + u2f(c[1].y)) + (u2f(c[2].y) + u2f(c[3].y))) + ((u2f(c[4].y) + u2f(c[5].y)) + (u2f(c[6].y) + u2f(c[7].y))), bfhi(xw2));
            uint32_t hi, lo;
            split2(x20 * g0, x21 * g1, hi, lo); sts1(ga_, hi); sts1(ga_ + 64, lo);
            split2(x20, x21, hi, lo); sts1(ga_ + 384, hi); sts1(ga_ + 448, lo);
            if ((tid >> 2) == b) sts2(sb + S_X2 + (tid & 3) * 8, __float_as_uint(x20), __float_as_uint(x21));
        }
        TS0(17);
        __syncwarp();
        const uint32_t va = sb + S_GVEC + warp * 1024 + g * 64 + q * 16;
        const uint4 bq0 = lds4(va), bq1 = lds4(va + 512);
        if (!have1) {
            mbar_wait(bars + (C_W1 + wg) * 8);
#pragma unroll
            for (int i = 0; i < 4; i++) ldsm4t(a0 + i * 512, af[i]);
        }
        float d0[4] = {0.f, 0.f, 0.f, 0.f}, d1[4] = {0.f, 0.f, 0.f, 0.f}, d2[4] = {0.f, 0.f, 0.f, 0.f}, d3[4] = {0.f, 0.f, 0.f, 0.f};
        mma16816(d0, af[0], bq0.x, bq0.y); mma16816(d1, af[1], bq0.z, bq0.w);
        mma16816(d2, af[2], bq1.x, bq1.y); mma16816(d3, af[3], bq1.z, bq1.w);
        float e0[4] = {0.f, 0.f, 0.f, 0.f}, e1[4] = {0.f, 0.f, 0.f, 0.f};
        {
            const uint32_t one = 0x3F803F80u;
            const uint32_t t0[4] = {bq0.x, one, bq0.y, one}, t1[4] = {bq0.z, one, bq0.w, one};
            const uint32_t t2[4] = {bq1.x, one, bq1.y, one}, t3[4] = {bq1.z, one, bq1.w, one};
            mma16816(e0, t0, bq0.x, bq0.y); mma16816(e1, t1, bq0.z, bq0.w);
            mma16816(e0, t2, bq1.x, bq1.y); mma16816(e1, t3, bq1.z, bq1.w);
        }
        {
            const bool st = q == 3;
            const float lo_ = fsel(st, (e0[0] + e0[1]) + (e1[0] + e1[1]), ((d0[0] + d0[1]) + (d1[0] + d1[1])) + ((d2[0] + d2[1]) + (d3[0] + d3[1])));
            const float hi_ = fsel(st, (e0[2] + e0[3]) + (e1[2] + e1[3]), ((d0[2] + d0[3]) + (d1[2] + d1[3])) + ((d2[2] + d2[3]) + (d3[2] + d3[3])));
            sts1f(sb + S_RED + q * 512 + g * 32 + warp * 4, lo_);
            sts1f(sb + S_RED + q * 512 + (g + 8) * 32 + warp * 4, hi_);
        }
        TS0(18);
        bar_arrive(9, 288);
        uint32_t w2r[16];
        mbar_wait2(bars + C_W2 * 8);
#pragma unroll
        for (int r = 0; r < 16; r++) w2r[r] = lds1(sb + S_W2 + r * 1024 + tid * 4);
        float w2f[32];
#pragma unroll
        for (int r = 0; r < 16; r++) { w2f[2 * r] = bflo(w2r[r]); w2f[2 * r + 1] = bfhi(w2r[r]); }
        bar_sync(10, b < 64 ? 320 : 288);
        float y0a = 0.f, y0b = 0.f, y1a = 0.f, y1b = 0.f;
#pragma unroll
        for (int r = 0; r < 16; r += 4) {
            const float4 f = lds4f(sb + S_STAT + r * 4);
            y0a = fmaf(f.x, w2f[2 * r], y0a); y1a = fmaf(f.x, w2f[2 * r + 1], y1a);
            y0b = fmaf(f.y, w2f[2 * r + 2], y0b); y1b = fmaf(f.y, w2f[2 * r + 3], y1b);
            y0a = fmaf(f.z, w2f[2 * r + 4], y0a); y1a = fmaf(f.z, w2f[2 * r + 5], y1a);
            y0b = fmaf(f.w, w2f[2 * r + 6], y0b); y1b = fmaf(f.w, w2f[2 * r + 7], y1b);
        }
        const uint32_t w0 = tagf(y0a + y0b, tg), w1 = tagf(y1a + y1b, tg);
        str2(d7, w0, w1); str2(d7 + 4096, w0, w1);
        TS0(19);
    }
}

__global__ void fb_gemv(const float* v, int vs, const __nv_bfloat16* W, size_t ws, size_t ks, size_t ns, int K, int N, float* out, float scale) {
    const int n = blockIdx.x * 8 + (threadIdx.x >> 5), z = blockIdx.y;
    if (n >= N) return;
    float s = 0.f;
    for (int k = threadIdx.x & 31; k < K; k += 32) s += v[(size_t)z * vs + k] * __bfloat162float(W[z * ws + k * ks + n * ns]);
    for (int o = 16; o; o >>= 1) s += __shfl_xor_sync(~0u, s, o);
    if ((threadIdx.x & 31) == 0) out[(size_t)z * N + n] = s * scale;
}
__device__ float fb_block_reduce(float v, bool mx, float* sh) {
    for (int o = 16; o; o >>= 1) { const float t = __shfl_xor_sync(~0u, v, o); v = mx ? fmaxf(v, t) : v + t; }
    __syncthreads();
    if ((threadIdx.x & 31) == 0) sh[threadIdx.x >> 5] = v;
    __syncthreads();
    v = sh[0];
    for (int i = 1; i < 16; i++) v = mx ? fmaxf(v, sh[i]) : v + sh[i];
    return v;
}
__global__ void fb_elem(int step, Params p, float* f) {
    __shared__ float sh[16];
    const int t = threadIdx.x;
    float* sc = f; float* mod = f + 512; float* hh = f + 4096; float* sco = f + 32768; float* o = f + 8192; float* x2 = f + 8704;
    float* ff = f + 9216; float* y = f + 11264;
    if (step == 0) { const float c = __bfloat162float(p.c[t]); sc[t] = c / (1.f + expf(-c)); }
    if (step == 1 || step == 3) {
        float x = __bfloat162float(p.x[t]);
        if (step == 3) { x += mod[1024 + t] * o[t]; x2[t] = x; }
        const float m = fb_block_reduce(x, false, sh) / 512.f, va = fb_block_reduce((x - m) * (x - m), false, sh) / 512.f;
        hh[t] = (x - m) * rsqrtf(va + 1e-5f) * (1.f + mod[(step == 1 ? 512 : 2048) + t]) + mod[(step == 1 ? 0 : 1536) + t];
    }
    if (step == 2) {
        float* r = sco + blockIdx.x * 8192;
        float m = -INFINITY, s = 0.f;
        for (int k = t; k < 8192; k += 512) m = fmaxf(m, r[k]);
        m = fb_block_reduce(m, true, sh);
        for (int k = t; k < 8192; k += 512) { r[k] = expf(r[k] - m); s += r[k]; }
        s = fb_block_reduce(s, false, sh);
        for (int k = t; k < 8192; k += 512) r[k] /= s;
    }
    if (step == 4)
        for (int n = t; n < 1376; n += 512) {
            const float a = ff[n] + __bfloat162float(p.b1[n]);
            ff[n] = 0.5f * a * (1.f + tanhf(0.7978845608f * (a + 0.044715f * a * a * a)));
        }
    if (step == 5) p.out[t] = __float2bfloat16(x2[t] + mod[2560 + t] * (y[t] + __bfloat162float(p.b2[t])));
}
void launch_fallback(const Params& p, void* const* d_in, cudaStream_t st) {
    typedef const __nv_bfloat16* W;
    float* f = reinterpret_cast<float*>(p.s + G_BYTES - (2 << 20) + 0);
    float *sc = f, *mod = f + 512, *hh = f + 4096, *q = f + 12288, *qa = f + 16384, *sco = f + 32768, *cc = f + 16384, *ctx = f + 12288;
    float *o = f + 8192, *ff = f + 9216, *y = f + 11264;
    fb_elem<<<1, 512, 0, st>>>(0, p, f);
    fb_gemv<<<dim3(384, 1), 256, 0, st>>>(sc, 0, (W)d_in[12], 0, 3072, 1, 512, 3072, mod, 1.f);
    fb_elem<<<1, 512, 0, st>>>(1, p, f);
    fb_gemv<<<dim3(512, 1), 256, 0, st>>>(hh, 0, (W)d_in[2], 0, 4096, 1, 512, 4096, q, 1.f);
    fb_gemv<<<dim3(64, 32), 256, 0, st>>>(q, 128, (W)d_in[3], 128, 1, 4096, 128, 512, qa, 0.08838834764831845f);
    fb_gemv<<<dim3(1024, 32), 256, 0, st>>>(qa, 512, (W)d_in[1], 0, 1, 512, 512, 8192, sco, 1.f);
    fb_elem<<<32, 512, 0, st>>>(2, p, f);
    fb_gemv<<<dim3(64, 32), 256, 0, st>>>(sco, 8192, (W)d_in[1], 0, 512, 1, 8192, 512, cc, 1.f);
    fb_gemv<<<dim3(16, 32), 256, 0, st>>>(cc, 512, (W)d_in[4], 128, 4096, 1, 512, 128, ctx, 1.f);
    fb_gemv<<<dim3(64, 1), 256, 0, st>>>(ctx, 0, (W)d_in[5], 0, 512, 1, 4096, 512, o, 1.f);
    fb_elem<<<1, 512, 0, st>>>(3, p, f);
    fb_gemv<<<dim3(172, 1), 256, 0, st>>>(hh, 0, (W)d_in[7], 0, 1376, 1, 512, 1376, ff, 1.f);
    fb_elem<<<1, 512, 0, st>>>(4, p, f);
    fb_gemv<<<dim3(64, 1), 256, 0, st>>>(ff, 0, (W)d_in[9], 0, 512, 1, 1376, 512, y, 1.f);
    fb_elem<<<1, 512, 0, st>>>(5, p, f);
}

typedef CUresult (*EncodeFn)(CUtensorMap*, CUtensorMapDataType, cuuint32_t, void*, const cuuint64_t*, const cuuint64_t*,
                             const cuuint32_t*, const cuuint32_t*, CUtensorMapInterleave, CUtensorMapSwizzle,
                             CUtensorMapL2promotion, CUtensorMapFloatOOBfill);

void make_map(EncodeFn enc, CUtensorMap* m, const void* ptr, uint64_t d0, uint64_t d1, uint64_t d2, uint64_t d3,
              uint64_t s1, uint64_t s2, uint64_t s3, uint32_t b0, uint32_t b1, uint32_t b2, uint32_t b3, CUtensorMapSwizzle sw) {
    cuuint64_t dims[4] = {d0, d1, d2, d3};
    cuuint64_t st[3] = {s1, s2, s3};
    cuuint32_t box[4] = {b0, b1, b2, b3};
    cuuint32_t es[4] = {1, 1, 1, 1};
    enc(m, CU_TENSOR_MAP_DATA_TYPE_BFLOAT16, 4, const_cast<void*>(ptr), dims, st, box, es, CU_TENSOR_MAP_INTERLEAVE_NONE, sw,
        CU_TENSOR_MAP_L2_PROMOTION_L2_128B, CU_TENSOR_MAP_FLOAT_OOB_FILL_NONE);
}

uint16_t g_tm[NTM] = {3880,7540,14905,350,420,600,700,280};
uint16_t g_sched[34] = {0,1070,1640,2185,2815,3410,3980,4525,5095,5665,6235,6745,7290,7885,8455,8965,9085,
                        9383,9803,9833,10503,11053,11885,12835,13135,15235,15255,15495,16605,17705,17785,18605,18655,0};

}

extern "C" void kernel_launch(void* const* d_in, const int* in_sizes, int n_in, void* d_out, int out_size) {
    (void)in_sizes; (void)n_in; (void)out_size;
    static EncodeFn enc = nullptr;
    static unsigned char* scratch = nullptr;
    static bool fused_ok = false;
    if (!scratch) {
        cudaGetSymbolAddress((void**)&scratch, g_scratch);
        scratch = (unsigned char*)(((uintptr_t)scratch + (2 << 20) - 1) & ~(uintptr_t)((2 << 20) - 1));
        void* fn = nullptr;
        cudaDriverEntryPointQueryResult qr;
        cudaGetDriverEntryPoint("cuTensorMapEncodeTiled", &fn, cudaEnableDefault, &qr);
        enc = (EncodeFn)fn;
        int clusters = 0;
        if (enc && cudaFuncSetAttribute(fused_decode_kernel, cudaFuncAttributeMaxDynamicSharedMemorySize, SMEM_BYTES) == cudaSuccess) {
            cudaLaunchConfig_t cfg = {};
            cfg.gridDim = dim3(NCTA); cfg.blockDim = dim3(NTHR); cfg.dynamicSmemBytes = SMEM_BYTES;
            cudaLaunchAttribute at[1];
            at[0].id = cudaLaunchAttributeClusterDimension; at[0].val.clusterDim.x = 2; at[0].val.clusterDim.y = 1; at[0].val.clusterDim.z = 1;
            cfg.attrs = at; cfg.numAttrs = 1;
            if (cudaOccupancyMaxActiveClusters(&clusters, fused_decode_kernel, &cfg) != cudaSuccess) clusters = 0;
        }
        (void)cudaGetLastError();
        fused_ok = clusters >= NCTA / 2;
    }
    Params p = {};
    p.x = (const __nv_bfloat16*)d_in[0];
    p.c = (const __nv_bfloat16*)d_in[11];
    p.b1 = (const __nv_bfloat16*)d_in[8];
    p.b2 = (const __nv_bfloat16*)d_in[10];
    p.out = (__nv_bfloat16*)d_out;
    p.s = scratch;
    for (int i = 0; i < NTM; i++) p.tm[i] = g_tm[i];
    for (int i = 0; i < 34; i++) p.sched[i] = g_sched[i];
    if (!fused_ok) { launch_fallback(p, d_in, cudaStreamPerThread); return; }
    const auto S128 = CU_TENSOR_MAP_SWIZZLE_128B, S32 = CU_TENSOR_MAP_SWIZZLE_32B, S64 = CU_TENSOR_MAP_SWIZZLE_64B, S0 = CU_TENSOR_MAP_SWIZZLE_NONE;
    make_map(enc, &p.m[0], d_in[12], 3072, 512, 1, 1, 6144, 6144 * 512, 6144 * 512, 16, 256, 1, 1, S32);
    make_map(enc, &p.m[1], d_in[2], 64, 512, 64, 1, 8192, 128, 8192 * 512, 64, 32, 2, 1, S128);
    make_map(enc, &p.m[2], d_in[3], 64, 512, 64, 1, 8192, 128, 8192 * 512, 64, 32, 2, 1, S128);
    make_map(enc, &p.m[3], d_in[1], 64, 8192, 8, 1, 1024, 128, 1024 * 8192, 64, 64, 1, 1, S128);
    make_map(enc, &p.m[4], d_in[4], 64, 64, 8, 64, 8192, 8192 * 64, 128, 64, 16, 2, 2, S128);
    make_map(enc, &p.m[5], d_in[5], 512, 4096, 1, 1, 1024, 1024 * 4096, 1024 * 4096, 32, 128, 1, 1, S64);
    make_map(enc, &p.m[8], d_in[12], 3072, 512, 1, 1, 6144, 6144 * 512, 6144 * 512, 32, 128, 1, 1, S64);
    make_map(enc, &p.m[6], d_in[7], 1376, 512, 1, 1, 2752, 2752 * 512, 2752 * 512, 16, 256, 1, 1, S32);
    make_map(enc, &p.m[7], d_in[9], 256, 2752, 1, 1, 512, 512 * 2752, 512 * 2752, 256, 16, 1, 1, S0);
    fused_decode_kernel<<<NCTA, NTHR, SMEM_BYTES, cudaStreamPerThread>>>(p);
}
```

```cpp
#include <cuda_runtime.h>
#include <cuda_bf16.h>
#include <cuda.h>
#include <stdint.h>

namespace {

constexpr int NCTA   = 128;
constexpr int NFFN   = 86;
constexpr int NCHUNK = 33;
constexpr int NTHR   = 384;

constexpr int C_MOD1 = 0, C_WQ = 1, C_WUK = 5, C_CKV = 9, C_T1 = 15, C_WUV = 19, C_W1 = 29, C_W2 = 31;
constexpr int C_MOD2 = 23, C_WO = 25;

constexpr int S_WQ   = 0;
constexpr int S_WUK  = 32768;
constexpr int S_CKV  = 65536;
constexpr int S_WUV  = 131072;
constexpr int S_WO   = 163840;
constexpr int S_MOD2 = 196608;
constexpr int S_MOD1 = 212992;
constexpr int S_SC   = 221184;
constexpr int S_RED  = 223232;
constexpr int S_VEC  = 227328;
constexpr int S_R16  = 227840;
constexpr int S_MAX  = 228352;
constexpr int S_ONES = 229376;
constexpr int S_ML   = 230400;
constexpr int S_X2   = 230400 + 384;
constexpr int S_STAT = 230912;
constexpr int S_BAR  = 230976;
constexpr int S_EP   = 231312;
constexpr int S_B4   = 230912;
constexpr int S_END  = 231328;
constexpr int S_QABS = S_WQ, S_XBUF1 = S_WQ + 24576, S_XBUF0 = S_MOD1, S_XCH = S_WUK, S_GVEC = S_WQ, S_FVEC = S_WQ + 8192;
constexpr int S_W1 = S_WUK, S_W2 = S_WUK + 16384, S_P = S_MOD1;
constexpr int B_UK = 33, B_QK = 34, B_X = 35, B_F = 37, B_BETA = 38, B_BETA4 = 39, B_W = 40, B_O = 41, NBAR = 42;
constexpr int SMEM_BYTES = S_END;

constexpr int WARM_T0 = 4200, WARM = 120;
constexpr int WIN = 5;
enum { T_H1 = 0, T_H3, T_H4, D_H5, D_H6, D_H7, D_H4, A_H4, NTM = 8 };

constexpr uint32_t G_H1 = 0;
constexpr uint32_t G_H6 = 192 << 10;
constexpr uint32_t G_MOD2 = 16 << 10;
constexpr uint32_t G_ML = 48 << 10;
constexpr uint32_t G_PROBE = 88 << 10;
constexpr uint32_t G_H3 = 128 << 10;
constexpr uint32_t G_H2 = 256 << 10;
constexpr uint32_t G_H5 = 384 << 10;
constexpr uint32_t G_H7 = 512 << 10;
constexpr uint32_t G_EPOCH = 1 << 20;
constexpr uint32_t G_H4 = 2 << 20;
constexpr uint32_t G_BYTES = 10 << 20;
__device__ __align__(256) unsigned char g_scratch[G_BYTES + (2 << 20)];
__device__ __forceinline__ uint32_t spread(uint32_t o) { return o + (o & ~4095u); }
__device__ __forceinline__ uint32_t pick(uint32_t po, uint32_t beta) {
    return po + (((beta ^ __popc(po & 0xB2000u)) & 1u) << 12);
}

struct Params {
    const __nv_bfloat16* x;
    const __nv_bfloat16* c;
    const __nv_bfloat16* b1;
    const __nv_bfloat16* b2;
    __nv_bfloat16* out;
    unsigned char* s;
    uint16_t tm[NTM];
    uint16_t sched[34];
    CUtensorMap m[9];
};

constexpr uint64_t POL_FIRST = 0x12F0000000000000ull, POL_NORMAL = 0x16F0000000000000ull;
constexpr int SPIN_MAX = 1 << 21;

__device__ __forceinline__ void mbar_init(uint32_t bar, uint32_t cnt) {
    asm volatile("mbarrier.init.shared::cta.b64 [%0], %1;" ::"r"(bar), "r"(cnt) : "memory");
}
__device__ __forceinline__ void mbar_expect_tx(uint32_t bar, uint32_t bytes) {
    asm volatile("mbarrier.arrive.expect_tx.shared::cta.b64 _, [%0], %1;" ::"r"(bar), "r"(bytes) : "memory");
}
__device__ __forceinline__ void mbar_arrive(uint32_t bar) {
    asm volatile("mbarrier.arrive.shared::cta.b64 _, [%0];" ::"r"(bar) : "memory");
}
__device__ __forceinline__ void mbar_wait(uint32_t bar) {
    asm volatile("{\n.reg .pred p;\nW:\nmbarrier.try_wait.parity.shared::cta.b64 p, [%0], 0;\n@!p bra W;\n}" ::"r"(bar) : "memory");
}
__device__ __forceinline__ void mbar_wait2(uint32_t bar) {
    asm volatile("{\n.reg .pred p, q;\nW:\n"
                 "mbarrier.try_wait.parity.shared::cta.b64 p, [%0], 0;\n"
                 "mbarrier.try_wait.parity.shared::cta.b64 q, [%0+8], 0;\n"
                 "and.pred p, p, q;\n@!p bra W;\n}" ::"r"(bar) : "memory");
}
__device__ __forceinline__ void mbar_wait4(uint32_t bar) {
    asm volatile("{\n.reg .pred p, q, r, s;\nW:\n"
                 "mbarrier.try_wait.parity.shared::cta.b64 p, [%0], 0;\n"
                 "mbarrier.try_wait.parity.shared::cta.b64 q, [%0+8], 0;\n"
                 "mbarrier.try_wait.parity.shared::cta.b64 r, [%0+16], 0;\n"
                 "mbarrier.try_wait.parity.shared::cta.b64 s, [%0+24], 0;\n"
                 "and.pred p, p, q;\nand.pred r, r, s;\nand.pred p, p, r;\n@!p bra W;\n}" ::"r"(bar) : "memory");
}
__device__ __forceinline__ void mbar_wait_cluster(uint32_t bar) {
    asm volatile("{\n.reg .pred p;\nW:\nmbarrier.try_wait.parity.acquire.cluster.shared::cta.b64 p, [%0], 0;\n@!p bra W;\n}" ::"r"(bar) : "memory");
}
__device__ __forceinline__ void tma4(uint32_t dst, const CUtensorMap* m, int c0, int c1, int c2, int c3, uint32_t bar, uint64_t pol) {
    asm volatile("cp.async.bulk.tensor.4d.shared::cluster.global.mbarrier::complete_tx::bytes.L2::cache_hint [%0], [%1, {%3,%4,%5,%6}], [%2], %7;"
                 ::"r"(dst), "l"(m), "r"(bar), "r"(c0), "r"(c1), "r"(c2), "r"(c3), "l"(pol) : "memory");
}
__device__ __forceinline__ void bar_sync(int id, int n) { asm volatile("bar.sync %0, %1;" ::"r"(id), "r"(n) : "memory"); }
__device__ __forceinline__ void bar_arrive(int id, int n) { asm volatile("bar.arrive %0, %1;" ::"r"(id), "r"(n) : "memory"); }
__device__ __forceinline__ void fence_async() { asm volatile("fence.proxy.async.shared::cta;" ::: "memory"); }

__device__ __forceinline__ uint32_t ldr1(const void* p) {
    uint32_t v; asm volatile("ld.relaxed.gpu.global.u32 %0, [%1];" : "=r"(v) : "l"(p) : "memory"); return v;
}
__device__ __forceinline__ uint2 ldr2(const void* p) {
    uint2 v; asm volatile("ld.relaxed.gpu.global.v2.u32 {%0,%1}, [%2];" : "=r"(v.x), "=r"(v.y) : "l"(p) : "memory"); return v;
}
__device__ __forceinline__ uint4 ldr4(const void* p) {
    uint4 v; asm volatile("ld.relaxed.gpu.global.v4.u32 {%0,%1,%2,%3}, [%4];"
                          : "=r"(v.x), "=r"(v.y), "=r"(v.z), "=r"(v.w) : "l"(p) : "memory"); return v;
}
__device__ __forceinline__ void str1(void* p, uint32_t v) { asm volatile("st.relaxed.gpu.global.u32 [%0], %1;" ::"l"(p), "r"(v) : "memory"); }
__device__ __forceinline__ void str2(void* p, uint32_t a, uint32_t b) {
    asm volatile("st.relaxed.gpu.global.v2.u32 [%0], {%1,%2};" ::"l"(p), "r"(a), "r"(b) : "memory");
}
__device__ __forceinline__ void str4(void* p, uint32_t a, uint32_t b, uint32_t c, uint32_t d) {
    asm volatile("st.relaxed.gpu.global.v4.u32 [%0], {%1,%2,%3,%4};" ::"l"(p), "r"(a), "r"(b), "r"(c), "r"(d) : "memory");
}
__device__ __forceinline__ void str64(void* p, uint32_t a, uint32_t b) {
    asm volatile("{\n.reg .b64 t;\nmov.b64 t, {%1,%2};\nst.relaxed.gpu.global.b64 [%0], t;\n}" ::"l"(p), "r"(a), "r"(b) : "memory");
}
__device__ __forceinline__ uint4 ldr64x2(const void* p) {
    uint4 v; asm volatile("{\n.reg .b64 s, t;\nld.relaxed.gpu.global.v2.b64 {s,t}, [%4];\nmov.b64 {%0,%1}, s;\nmov.b64 {%2,%3}, t;\n}"
                          : "=r"(v.x), "=r"(v.y), "=r"(v.z), "=r"(v.w) : "l"(p) : "memory"); return v;
}
__device__ __forceinline__ uint32_t tagf(float v, uint32_t tg) {
    uint32_t r; asm("lop3.b32 %0, %1, 0xFFFFFFFE, %2, 0xEA;" : "=r"(r) : "r"(__float_as_uint(v)), "r"(tg)); return r;
}
__device__ __forceinline__ float u2f(uint32_t v) { return __uint_as_float(v); }

__device__ __forceinline__ void sts1(uint32_t a, uint32_t v) { asm volatile("st.shared.u32 [%0], %1;" ::"r"(a), "r"(v) : "memory"); }
__device__ __forceinline__ void sts1f(uint32_t a, float v) { asm volatile("st.shared.f32 [%0], %1;" ::"r"(a), "f"(v) : "memory"); }
__device__ __forceinline__ void stsh(uint32_t a, uint32_t v) { asm volatile("st.shared.u16 [%0], %1;" ::"r"(a), "h"((unsigned short)v) : "memory"); }
__device__ __forceinline__ void sts2(uint32_t a, uint32_t x, uint32_t y) { asm volatile("st.shared.v2.u32 [%0], {%1,%2};" ::"r"(a), "r"(x), "r"(y) : "memory"); }
__device__ __forceinline__ void sts4(uint32_t a, uint32_t x, uint32_t y, uint32_t z, uint32_t w) {
    asm volatile("st.shared.v4.u32 [%0], {%1,%2,%3,%4};" ::"r"(a), "r"(x), "r"(y), "r"(z), "r"(w) : "memory");
}
__device__ __forceinline__ uint32_t lds1(uint32_t a) { uint32_t v; asm volatile("ld.shared.u32 %0, [%1];" : "=r"(v) : "r"(a) : "memory"); return v; }
__device__ __forceinline__ float lds1f(uint32_t a) { float v; asm volatile("ld.shared.f32 %0, [%1];" : "=f"(v) : "r"(a) : "memory"); return v; }
__device__ __forceinline__ float2 lds2f(uint32_t a) { float2 v; asm volatile("ld.shared.v2.f32 {%0,%1}, [%2];" : "=f"(v.x), "=f"(v.y) : "r"(a) : "memory"); return v; }
__device__ __forceinline__ uint4 lds4(uint32_t a) {
    uint4 v; asm volatile("ld.shared.v4.u32 {%0,%1,%2,%3}, [%4];" : "=r"(v.x), "=r"(v.y), "=r"(v.z), "=r"(v.w) : "r"(a) : "memory"); return v;
}
__device__ __forceinline__ float4 lds4f(uint32_t a) {
    float4 v; asm volatile("ld.shared.v4.f32 {%0,%1,%2,%3}, [%4];" : "=f"(v.x), "=f"(v.y), "=f"(v.z), "=f"(v.w) : "r"(a) : "memory"); return v;
}
__device__ __forceinline__ void ldsm4(uint32_t a, uint32_t (&r)[4]) {
    asm volatile("ldmatrix.sync.aligned.m8n8.x4.shared.b16 {%0,%1,%2,%3}, [%4];"
                 : "=r"(r[0]), "=r"(r[1]), "=r"(r[2]), "=r"(r[3]) : "r"(a) : "memory");
}
__device__ __forceinline__ void ldsm4t(uint32_t a, uint32_t (&r)[4]) {
    asm volatile("ldmatrix.sync.aligned.m8n8.x4.trans.shared.b16 {%0,%1,%2,%3}, [%4];"
                 : "=r"(r[0]), "=r"(r[1]), "=r"(r[2]), "=r"(r[3]) : "r"(a) : "memory");
}
__device__ __forceinline__ void stsm4t(uint32_t a, uint32_t r0, uint32_t r1, uint32_t r2, uint32_t r3) {
    asm volatile("stmatrix.sync.aligned.m8n8.x4.trans.shared.b16 [%0], {%1,%2,%3,%4};"
                 ::"r"(a), "r"(r0), "r"(r1), "r"(r2), "r"(r3) : "memory");
}
__device__ __forceinline__ void mma16816(float (&d)[4], const uint32_t (&a)[4], uint32_t b0, uint32_t b1) {
    asm volatile("mma.sync.aligned.m16n8k16.row.col.f32.bf16.bf16.f32 {%0,%1,%2,%3}, {%4,%5,%6,%7}, {%8,%9}, {%0,%1,%2,%3};"
                 : "+f"(d[0]), "+f"(d[1]), "+f"(d[2]), "+f"(d[3])
                 : "r"(a[0]), "r"(a[1]), "r"(a[2]), "r"(a[3]), "r"(b0), "r"(b1));
}
__device__ __forceinline__ uint32_t packbf(float lo, float hi) {
    uint32_t r; asm("cvt.rn.bf16x2.f32 %0, %1, %2;" : "=r"(r) : "f"(hi), "f"(lo)); return r;
}
__device__ __forceinline__ float bflo(uint32_t w) { return __uint_as_float(w << 16); }
__device__ __forceinline__ float bfhi(uint32_t w) { return __uint_as_float(w & 0xffff0000u); }
__device__ __forceinline__ void split2(float a, float b, uint32_t& hi, uint32_t& lo) {
    hi = packbf(a, b);
    lo = packbf(a - bflo(hi), b - bfhi(hi));
}
__device__ __forceinline__ uint32_t ordf(uint32_t u) { return u ^ ((uint32_t)((int)u >> 31) & 0x7FFFFFFFu); }
__device__ __forceinline__ void red_max(uint32_t a, uint32_t v) { asm volatile("red.shared.max.s32 [%0], %1;" ::"r"(a), "r"(v) : "memory"); }
__device__ __forceinline__ float fsel(bool c, float a, float b) {
    float r; asm("{\n.reg .pred p;\nsetp.ne.b32 p, %3, 0;\nselp.f32 %0, %1, %2, p;\n}" : "=f"(r) : "f"(a), "f"(b), "r"((int)c)); return r;
}
__device__ __forceinline__ float ex2(float x) { float y; asm("ex2.approx.ftz.f32 %0, %1;" : "=f"(y) : "f"(x)); return y; }

__device__ __forceinline__ int vpos(int k32) {
    return (((k32 & 7) >> 1) * 8 + (k32 >> 4) * 4 + ((k32 >> 3) & 1) * 2 + (k32 & 1)) * 2;
}

__device__ __forceinline__ void wg_fence()  { asm volatile("wgmma.fence.sync.aligned;" ::: "memory"); }
__device__ __forceinline__ void wg_commit() { asm volatile("wgmma.commit_group.sync.aligned;" ::: "memory"); }
template <int N> __device__ __forceinline__ void wg_wait() { asm volatile("wgmma.wait_group.sync.aligned %0;" ::"n"(N) : "memory"); }
__device__ __forceinline__ uint64_t mkdesc(uint32_t addr) {
    return (uint64_t)((addr & 0x3FFFF) >> 4) | ((uint64_t)64 << 16) | ((uint64_t)64 << 32) | ((uint64_t)1 << 62);
}
template <int TA>
__device__ __forceinline__ void wgmma_n32(float (&d)[16], uint64_t da, uint64_t db, int acc) {
    asm volatile("{\n.reg .pred p;\nsetp.ne.b32 p, %18, 0;\n"
                 "wgmma.mma_async.sync.aligned.m64n32k16.f32.bf16.bf16 "
                 "{%0,%1,%2,%3,%4,%5,%6,%7,%8,%9,%10,%11,%12,%13,%14,%15}, %16, %17, p, 1, 1, %19, 0;\n}"
                 : "+f"(d[0]), "+f"(d[1]), "+f"(d[2]), "+f"(d[3]), "+f"(d[4]), "+f"(d[5]), "+f"(d[6]), "+f"(d[7]),
                   "+f"(d[8]), "+f"(d[9]), "+f"(d[10]), "+f"(d[11]), "+f"(d[12]), "+f"(d[13]), "+f"(d[14]), "+f"(d[15])
                 : "l"(da), "l"(db), "r"(acc), "n"(TA));
}
__device__ __forceinline__ void reg_fence16(float (&d)[16]) {
#pragma unroll
    for (int i = 0; i < 16; i++) asm volatile("" : "+f"(d[i])::"memory");
}

template <bool TRANS>
__device__ __forceinline__ void gemv128(uint32_t tile, uint32_t vec, uint32_t bars, int warp, int lane, float& r0, float& r1) {
    const int m = lane >> 3, r8 = lane & 7;
    uint32_t bq[4][4];
#pragma unroll
    for (int i = 0; i < 4; i++) {
        uint4 t = lds4(vec + i * 128 + ((lane >> 2) & 1) * 64 + (lane & 3) * 16);
        bq[i][0] = t.x; bq[i][1] = t.y; bq[i][2] = t.z; bq[i][3] = t.w;
    }
    float d0[4] = {0.f, 0.f, 0.f, 0.f}, d1[4] = {0.f, 0.f, 0.f, 0.f};
    if (TRANS) {
        const uint32_t a0 = tile + (warp >> 2) * 4096 + ((m >> 1) * 8 + r8) * 128 + ((((warp & 3) * 2 + (m & 1)) ^ r8) << 4);
#pragma unroll
        for (int i = 0; i < 4; i++) {
            mbar_wait(bars + i * 8);
            uint32_t a[4], c[4];
            ldsm4t(a0 + i * 8192, a);
            ldsm4t(a0 + i * 8192 + 2048, c);
            mma16816(d0, a, bq[i][0], bq[i][1]);
            mma16816(d1, c, bq[i][2], bq[i][3]);
        }
    } else {
        mbar_wait(bars + (warp >> 1) * 8);
        const uint32_t a0 = tile + (warp >> 1) * 8192 + ((warp & 1) * 16 + (m & 1) * 8 + r8) * 128;
#pragma unroll
        for (int i = 0; i < 4; i++) {
            uint32_t a[4], c[4];
            ldsm4(a0 + (i >> 1) * 4096 + ((((i & 1) * 4 + (m >> 1)) ^ r8) << 4), a);
            ldsm4(a0 + (i >> 1) * 4096 + ((((i & 1) * 4 + 2 + (m >> 1)) ^ r8) << 4), c);
            mma16816(d0, a, bq[i][0], bq[i][1]);
            mma16816(d1, c, bq[i][2], bq[i][3]);
        }
    }
    r0 = (d0[0] + d0[1]) + (d1[0] + d1[1]);
    r1 = (d0[2] + d0[3]) + (d1[2] + d1[3]);
}

__device__ __forceinline__ void step32(uint32_t rows, uint32_t vecaddr, int lane, float (&d0)[4], float (&d1)[4]) {
    const int m = lane >> 3, r8 = lane & 7;
    const uint32_t a0 = rows + ((m >> 1) * 8 + r8) * 32 + (((m & 1) ^ (r8 >> 2)) << 4);
    uint4 t = lds4(vecaddr);
    uint32_t a[4], c[4];
    ldsm4t(a0, a);
    ldsm4t(a0 + 512, c);
    mma16816(d0, a, t.x, t.y);
    mma16816(d1, c, t.z, t.w);
}

__device__ __forceinline__ void reduce16_publish(uint32_t sb, float (&d0)[4], float (&d1)[4], int tid, int warp, int lane, unsigned char* dst, uint32_t tg) {
    if ((lane & 3) == 0) {
        sts1f(sb + S_R16 + (lane >> 2) * 32 + warp * 4, (d0[0] + d0[1]) + (d1[0] + d1[1]));
        sts1f(sb + S_R16 + ((lane >> 2) + 8) * 32 + warp * 4, (d0[2] + d0[3]) + (d1[2] + d1[3]));
    }
    bar_sync(2, 256);
    if (tid < 32) {
        float4 u = lds4f(sb + S_R16 + (tid & 15) * 32), v = lds4f(sb + S_R16 + (tid & 15) * 32 + 16);
        str1(dst + (tid & 15) * 4 + (tid >> 4) * 4096, tagf(((u.x + u.y) + (u.z + u.w)) + ((v.x + v.y) + (v.z + v.w)), tg));
    }
}

__device__ __forceinline__ uint32_t xo2(uint32_t a, uint32_t b, uint32_t t) {
    uint32_t r; asm("lop3.b32 %0, %1, %2, %3, 0x7E;" : "=r"(r) : "r"(a), "r"(b), "r"(t)); return r;
}
__device__ __forceinline__ uint32_t or3(uint32_t a, uint32_t b, uint32_t c) {
    uint32_t r; asm("lop3.b32 %0, %1, %2, %3, 0xFE;" : "=r"(r) : "r"(a), "r"(b), "r"(c)); return r;
}
__device__ __forceinline__ uint32_t bad2(const uint2& v, uint32_t tg) { return xo2(v.x, v.y, tg); }
__device__ __forceinline__ uint32_t bad4(const uint4& v, uint32_t tg) { return or3(xo2(v.x, v.y, tg), xo2(v.z, v.w, tg), 0); }
__device__ __forceinline__ bool nz4(const uint4& v) { return v.x != 0 && v.y != 0 && v.z != 0 && v.w != 0; }
__device__ __forceinline__ uint32_t clk32() { uint32_t c; asm volatile("mov.u32 %0, %%clock;" : "=r"(c)); return c; }
__device__ __forceinline__ void wait_until(uint32_t t0, uint32_t dt) {
#pragma unroll 1
    while ((int)(clk32() - t0 - dt) < 0) {}
}
__device__ __forceinline__ uint32_t mbar_mask4(uint32_t bar) {
    uint32_t m;
    asm volatile("{\n.reg .pred p, q, r, s;\n.reg .b32 a, b;\n"
                 "mbarrier.test_wait.parity.shared::cta.b64 p, [%1], 0;\n"
                 "mbarrier.test_wait.parity.shared::cta.b64 q, [%1+8], 0;\n"
                 "mbarrier.test_wait.parity.shared::cta.b64 r, [%1+16], 0;\n"
                 "mbarrier.test_wait.parity.shared::cta.b64 s, [%1+24], 0;\n"
                 "selp.u32 a, 1, 0, p;\nselp.u32 b, 2, 0, q;\nor.b32 a, a, b;\nselp.u32 b, 4, 0, r;\nor.b32 a, a, b;\n"
                 "selp.u32 b, 8, 0, s;\nor.b32 a, a, b;\nredux.sync.and.b32 %0, a, 0xffffffff;\n}" : "=r"(m) : "r"(bar) : "memory");
    return m;
}
__device__ __forceinline__ uint32_t probe_near(unsigned char* sp, uint32_t po, uint32_t sink) {
    uint32_t best0 = ~0u, best1 = ~0u;
#pragma unroll 1
    for (int r = 0; r < 5; r++) {
        uint32_t v; const uint32_t t0 = clk32();
        asm volatile("atom.relaxed.gpu.global.exch.b32 %0, [%1], %2;" : "=r"(v) : "l"(sp + po + (r & 1) * 4096), "r"(r) : "memory");
        sts1(sink, v);
        const uint32_t dt = clk32() - t0;
        if (r & 1) best1 = min(best1, dt); else best0 = min(best0, dt);
    }
    return (uint32_t)(best1 < best0) ^ (__popc(po & 0xB2000u) & 1u);
}
#define PIN(x) asm volatile("" : "+l"(x))
#define SPIN_CHECK(it) if (++(it) > SPIN_MAX) __trap()

__device__ __forceinline__ void mod2_tile(uint32_t sb, unsigned char* sp, uint32_t bars, int b, int nt, int lane, uint32_t tg) {
    const int m = lane >> 3, r8 = lane & 7, q = lane & 3;
    const uint32_t a0 = sb + S_MOD2 + ((m >> 1) * 8 + r8) * 64 + (((nt * 2 + (m & 1)) ^ (r8 >> 1)) << 4);
    const uint32_t v0 = sb + S_SC + (b >> 6) * 1024 + ((lane >> 2) & 1) * 64 + q * 16;
    float d0[4] = {0.f, 0.f, 0.f, 0.f}, d1[4] = {0.f, 0.f, 0.f, 0.f};
#pragma unroll 1
    for (int c = 0; c < 2; c++) {
        mbar_wait(bars + (C_MOD2 + c) * 8);
#pragma unroll
        for (int i = 0; i < 4; i++) {
            const uint4 t = lds4(v0 + (c * 4 + i) * 128);
            uint32_t a[4], e[4];
            ldsm4t(a0 + c * 8192 + i * 2048, a); ldsm4t(a0 + c * 8192 + i * 2048 + 1024, e);
            mma16816(d0, a, t.x, t.y); mma16816(d1, e, t.z, t.w);
        }
    }
    const float r0 = (d0[0] + d0[1]) + (d1[0] + d1[1]), r1 = (d0[2] + d0[3]) + (d1[2] + d1[3]);
    const float t0 = __shfl_sync(~0u, r0, lane & 28), t1 = __shfl_sync(~0u, r1, lane & 28);
    str1(sp + G_MOD2 + spread(b * 128 + nt * 64 + (q & 1) * 32 + (lane >> 2) * 4) + (q >> 1) * 4096, tagf((q & 1) ? t1 : t0, tg));
}

__global__ void __cluster_dims__(2, 1, 1) __launch_bounds__(NTHR, 1) fused_decode_kernel(const __grid_constant__ Params p) {
    extern __shared__ __align__(1024) unsigned char smem_raw[];
    const uint32_t sb = (uint32_t)__cvta_generic_to_shared(smem_raw);
    const int tid = threadIdx.x, lane = tid & 31;
    const int warp = __shfl_sync(~0u, tid >> 5, 0);
    const int b = blockIdx.x, h = b >> 2, j = b & 3, rank = b & 1, pair = b >> 1;
    const uint32_t bars = sb + S_BAR;
    unsigned char* const sp = p.s;
    const uint32_t t_start = clk32();

    if (warp == 11) {
        float d[4] = {0.f, 0.f, 0.f, 0.f};
        const uint32_t zz = t_start & 0x00010001u, z[4] = {zz, zz, zz, zz};
        mma16816(d, z, zz, zz);
        bar_sync(1, NTHR - 64);
        uint32_t done = 0;
#pragma unroll 1
        for (int i = 0; i < 4096 && done < 2; i++) {
            mma16816(d, z, zz, zz);
            __nanosleep(200);
            done += mbar_mask4(bars + B_F * 8) & 1;
        }
        if (d[0] == 1.f) sts1f(sb + S_EP + 12, d[1]);
        return;
    }
    if (warp == 8) {
        if (lane == 0) {
            mbar_init(bars, 1);
            asm volatile("fence.mbarrier_init.release.cluster;" ::: "memory");
            mbar_expect_tx(bars, 8192);
            tma4(sb + S_MOD1, &p.m[0], (b >> 1) * 16, (b & 1) * 256, 0, 0, bars, POL_FIRST);
#pragma unroll
            for (int i = 1; i < NBAR; i++) mbar_init(bars + i * 8, i == B_UK ? 8 : i == B_O ? 4 : 1);
            asm volatile("fence.mbarrier_init.release.cluster;" ::: "memory");
            mbar_expect_tx(bars + B_X * 8, 8192); mbar_expect_tx(bars + (B_X + 1) * 8, 8192);
        }
        __syncwarp();
        bar_arrive(1, NTHR - 64);
        {
            const int c = lane + 1;
            int mi = 1, k = c - C_WQ, c0 = 0, c1 = j * 128, d1 = 32, c2 = h * 2, c3 = 0, dst = S_WQ;
            if (c >= C_WUK)  { mi = 2; k = c - C_WUK; dst = S_WUK; }
            if (c >= C_CKV)  { mi = 3; k = c - C_CKV; dst = S_CKV; c1 = pair * 128 + (k >> 2) * 64; d1 = 0; c2 = rank * 4 + (k & 3); }
            if (c >= C_T1)   { const int x = (c - C_T1) & 1; k = (c - C_T1) >> 1; dst = x ? S_XCH : S_CKV + 6 * 8192; c1 = pair * 128 + 64; c2 = (rank ^ x) * 4 + 2 + k; }
            if (c >= C_WUV)  { mi = 4; k = c - C_WUV; dst = S_WUV; c1 = j * 16; c2 = k * 2; c3 = h * 2; }
            if (c >= C_WUV + 4) { mi = 5; k = c - C_WO; dst = S_WO; c0 = (b & 15) * 32; c1 = (b >> 4) * 512; d1 = 128; c2 = 0; c3 = 0; }
            if (c == C_MOD2 || c == C_MOD2 + 1) { mi = 8; k = c - C_MOD2; dst = S_MOD2; c0 = 1024 + (b & 63) * 32; c1 = (b >> 6) * 256; }
            if (c >= C_W1)   { mi = 6; k = c - C_W1; dst = S_W1; c0 = b * 16; c1 = 0; d1 = 256; }
            if (c >= C_W2)   { mi = 7; k = c - C_W2; dst = S_W2; c0 = 0; c1 = b * 32; d1 = 16; }
            const uint32_t wa = (uint32_t)c0 | (uint32_t)(c1 + k * d1) << 16;
            const bool keep = c >= C_T1 && c < C_WUV;
            const uint32_t wb = (uint32_t)c2 | (uint32_t)c3 << 8 | (uint32_t)mi << 14 | (uint32_t)keep << 18 | (uint32_t)((dst >> 13) + k) << 24;
            const int nch = b < NFFN ? NCHUNK : C_W1;
#pragma unroll 1
            for (int i = 1; i < nch; i++) {
                const uint32_t ua = __shfl_sync(~0u, wa, i - 1), ub = __shfl_sync(~0u, wb, i - 1);
                if (i == C_T1 + 1) mbar_wait(bars + B_UK * 8);
                if (i == C_W1) mbar_wait(bars + B_QK * 8);
                if (i >= WIN) mbar_wait(bars + (i - WIN) * 8);
                wait_until(t_start, p.sched[i]);
                if (lane == 0) {
                    mbar_expect_tx(bars + i * 8, 8192);
                    tma4(sb + (ub >> 24) * 8192, &p.m[(ub >> 14) & 15], ua & 0xffff, ua >> 16, ub & 0xff, (ub >> 8) & 0x3f, bars + i * 8,
                         (ub >> 18 & 1) ? POL_NORMAL : POL_FIRST);
                }
            }
        }
        return;
    }
    if (warp == 9) {
        const int col = (lane & 1) * 4 + (lane & 2) + ((lane >> 2) & 1);
        const float be = __bfloat162float(p.b2[(b & 63) * 8 + col]);
        const uint32_t pr0 = G_PROBE + b * 32;
        if (lane < 4) str4(sp + pr0 + (lane & 2) * 2048 + (lane & 1) * 16, 0, 0, 0, 0);
        __syncwarp();
        uint32_t beta = 0;
        if (lane == 0) { beta = probe_near(sp, pr0, sb + S_EP + 12); sts1(sb + S_EP + 4, beta); }
        __syncwarp();
        bar_sync(8, 64);
        if (lane == 0) mbar_arrive(bars + B_BETA * 8);
        const uint32_t ep = lds1(sb + S_EP);
        const uint32_t tg = ~ep & 1u;
        beta = __shfl_sync(~0u, beta, 0);
        const unsigned char* sg = sp + pick(G_MOD2 + spread((lane & 8) * 1024 + 6144 + (b & 63) * 32 + col * 4), beta);
        const unsigned char* s7 = sp + pick(G_H7 + (b & 63) * 8192 + lane * 16, beta);
        const unsigned char* s7c = s7 + (lane < 2 * (NFFN - 80) ? 2560 : 0);
        mod2_tile(sb, sp, bars, b, 0, lane, tg);
        if (b >= 64) return;
        mbar_wait(bars + B_F * 8);
        uint32_t w; int it = 0;
#pragma unroll 1
        do { w = ldr1(sg); SPIN_CHECK(it); } while (__any_sync(~0u, (w ^ tg) & 1));
        const float gb = u2f(w) + __shfl_xor_sync(~0u, u2f(w), 8);
        bar_sync(10, 320);
        const uint32_t t_6 = clk32();
        const float x2 = fmaf(gb, be, lds1f(sb + S_X2 + col * 4));
        wait_until(t_6, p.tm[D_H7]);
        uint4 y[6];
#pragma unroll 1
        do {
#pragma unroll
            for (int i = 0; i < 5; i++) y[i] = ldr4(s7 + i * 512);
            y[5] = ldr4(s7c);
            SPIN_CHECK(it);
        } while (__any_sync(~0u, or3(or3(bad4(y[0], tg), bad4(y[1], tg), bad4(y[2], tg)), or3(bad4(y[3], tg), bad4(y[4], tg), bad4(y[5], tg)), 0) & 1));
        if (lane >= 2 * (NFFN - 80)) y[5] = make_uint4(0, 0, 0, 0);
        const float s0 = ((u2f(y[0].x) + u2f(y[1].x)) + (u2f(y[2].x) + u2f(y[3].x))) + (u2f(y[4].x) + u2f(y[5].x));
        const float s1 = ((u2f(y[0].y) + u2f(y[1].y)) + (u2f(y[2].y) + u2f(y[3].y))) + (u2f(y[4].y) + u2f(y[5].y));
        const float s2 = ((u2f(y[0].z) + u2f(y[1].z)) + (u2f(y[2].z) + u2f(y[3].z))) + (u2f(y[4].z) + u2f(y[5].z));
        const float s3 = ((u2f(y[0].w) + u2f(y[1].w)) + (u2f(y[2].w) + u2f(y[3].w))) + (u2f(y[4].w) + u2f(y[5].w));
        {
            const bool b1 = lane & 2, b2 = lane & 4;
            const float k0 = (b1 ? s2 : s0) + __shfl_xor_sync(~0u, b1 ? s0 : s2, 2), k1 = (b1 ? s3 : s1) + __shfl_xor_sync(~0u, b1 ? s1 : s3, 2);
            float k = (b2 ? k1 : k0) + __shfl_xor_sync(~0u, b2 ? k0 : k1, 4);
            k += __shfl_xor_sync(~0u, k, 8); k += __shfl_xor_sync(~0u, k, 16);
            if (lane < 8) p.out[b * 8 + col] = __float2bfloat16(fmaf(gb, k, x2));
            if (b == 0 && lane == 8) str1(sp + G_EPOCH, ep + 1);
        }
        return;
    }

    if (warp == 10) {
        const float b1v = __bfloat162float(p.b1[(b < NFFN ? b * 16 : 0) + (lane & 15)]);
        const uint32_t pr4 = G_H4 + pair * 131072 + 65536 + rank * 256;
        const uint32_t prev = ldr1(sp + pr4 + 128);
        if (lane < 4) str4(sp + pr4 + (lane & 2) * 2048 + (lane & 1) * 16, 0, 0, 0, 0);
        __syncwarp();
        uint32_t beta4 = 0;
        if (lane == 0) beta4 = probe_near(sp, pr4, sb + S_X2);
        beta4 = __shfl_sync(~0u, beta4, 0);
        bar_sync(11, 64);
        const uint32_t tg = ~lds1(sb + S_EP) & 1u;
        {
            const uint32_t held = (prev & 24) ^ (8u << beta4), t4 = held >> (3 + beta4) & 1;
            const uint32_t w = tg | beta4 << 1 | t4 << 2 | held;
            if (lane < 2) str4(sp + pr4 + 128 + lane * 16, w, w, w, w);
            if (lane == 0) sts1(sb + S_EP + 8, w);
#pragma unroll 1
            for (int i = 0; i < 32; i++) {
                wait_until(t_start, WARM_T0 + i * WARM);
                str4(sp + pick(G_H4 + pair * 131072 + spread((i * 4 + (lane >> 3)) * 256 + rank * 128 + (lane & 7) * 16), beta4), t4 ^ 1, 0, t4 ^ 1, 0);
            }
            __syncwarp();
            if (lane == 0) mbar_arrive(bars + B_BETA4 * 8);
        }
        mbar_wait(bars + B_BETA * 8);
        const uint32_t beta = lds1(sb + S_EP + 4);
        const unsigned char* sm_a = sp + pick(G_ML + spread(lane * 256 + h * 4), beta);
        const unsigned char* sm_b = sp + pick(G_ML + spread((lane + 32) * 256 + h * 4), beta);
        mbar_wait(bars + B_O * 8);
        wait_until(clk32() - p.tm[A_H4] - 40, p.tm[D_H4]);
        wait_until(t_start, p.tm[T_H4] - p.tm[A_H4] - 40);
        uint32_t ma, mb, la, lb; int it = 0;
#pragma unroll 1
        do {
            ma = ldr1(sm_a); mb = ldr1(sm_b); la = ldr1(sm_a + 128); lb = ldr1(sm_b + 128);
            SPIN_CHECK(it);
        } while (__any_sync(~0u, (xo2(ma, mb, tg) | xo2(la, lb, tg)) & 1));
        const float M = u2f(ordf(__reduce_max_sync(~0u, max((int)ordf(ma), (int)ordf(mb)))));
        const float wa = ex2(u2f(ma) - M), wb = ex2(u2f(mb) - M);
        const float L = __fdividef(262144.f, __uint2float_rn(__reduce_add_sync(~0u, __float2uint_rn(fmaf(wa, u2f(la), wb * u2f(lb)) * 262144.f))));
        sts1f(sb + S_ML + lane * 4, wa * L); sts1f(sb + S_ML + 128 + lane * 4, wb * L);
        __syncwarp();
        if (lane == 0) mbar_arrive(bars + B_W * 8);
        mod2_tile(sb, sp, bars, b, 1, lane, tg);
        if (b < NFFN) {
            const uint32_t a = sb + S_RED + (lane & 15) * 32 + (lane >> 4) * 16;
            const uint32_t as = sb + S_RED + 1536 + (lane >> 4) * 16;
            bar_sync(9, 288);
            const float4 sa = lds4f(as + 8 * 32), ta = lds4f(as + 6 * 32), tc = lds4f(as + 7 * 32);
            const float4 U = lds4f(a), G = lds4f(a + 512), S = lds4f(a + 1024);
            float mu = (sa.x + sa.y) + (sa.z + sa.w), ex = ((ta.x + ta.y) + (ta.z + ta.w)) + ((tc.x + tc.y) + (tc.z + tc.w));
            float us = (U.x + U.y) + (U.z + U.w), gs = (G.x + G.y) + (G.z + G.w), ss = (S.x + S.y) + (S.z + S.w);
            mu += __shfl_xor_sync(~0u, mu, 16); ex += __shfl_xor_sync(~0u, ex, 16);
            us += __shfl_xor_sync(~0u, us, 16); gs += __shfl_xor_sync(~0u, gs, 16); ss += __shfl_xor_sync(~0u, ss, 16);
            mu *= 1.f / 512.f;
            float rstd;
            asm("rsqrt.approx.ftz.f32 %0, %1;" : "=f"(rstd) : "f"(fmaxf(fmaf(ex, 1.f / 512.f, -mu * mu), 0.f) + 1e-5f));
            const float pre = (us - mu * gs) * rstd + (ss + b1v);
            float th;
            asm("tanh.approx.f32 %0, %1;" : "=f"(th) : "f"(pre * fmaf(pre * pre, 0.044715f * 0.7978845608f, 0.7978845608f)));
            sts1f(sb + S_STAT + (lane & 15) * 4, fmaf(0.5f * pre, th, 0.5f * pre));
            bar_arrive(10, b < 64 ? 320 : 288);
        }
        return;
    }

    const int g = lane >> 2, q = lane & 3;
    const int wg = warp >> 2, wq = warp & 3;
    const uint32_t ep0 = ldr1(sp + G_EPOCH);
    const uint32_t tg = ~ep0 & 1u;
    const uint32_t cw = *reinterpret_cast<const uint32_t*>(p.c + tid * 2);
    const uint4 xa = *reinterpret_cast<const uint4*>(p.x + lane * 16), xb = *reinterpret_cast<const uint4*>(p.x + lane * 16 + 8);
    const uint32_t xw2 = *reinterpret_cast<const uint32_t*>(p.x + tid * 2);
    const float xm = __bfloat162float(p.x[j * 128 + (tid & 127)]);
    {
        uint32_t z = ~0u, zv = tg ^ 1u;
        if (tid < 4) z = G_H1 + spread((b & 1) * 4096 + (b >> 1) * 64 + tid * 16);
        else if (tid >= 8 && tid < 16) z = G_MOD2 + spread(b * 128 + (tid & 7) * 16);
        else if (tid >= 112 && tid < 120) z = G_H6 + spread(b * 128 + (tid & 7) * 16);
        else if (tid >= 16 && tid < 32) { const uint32_t o = G_ML + spread(pair * 256 + (tid & 15) * 16) + rank * 4096; str4(sp + o, zv, zv, zv, zv); }
        else if (tid >= 32 && tid < 64) z = G_H2 + spread(b * 512 + lane * 16);
        else if (tid >= 64 && tid < 96) z = G_H5 + spread(b * 512 + lane * 16);
        else if (tid >= 96 && tid < 112) { z = G_H3 + spread((j * 2 + ((tid >> 3) & 1)) * 4096 + h * 128 + (tid & 7) * 16); zv = 0; }
        if (z != ~0u) { str4(sp + z, zv, zv, zv, zv); str4(sp + z + 4096, zv, zv, zv, zv); }
    }
    if (tid == 0) sts1(sb + S_EP, ep0);
    if (tid < 64) sts1(sb + S_MAX + tid * 4, 0x80000000u);
    sts1(sb + S_ONES + tid * 4, 0x3F803F80u);
    {
        const float c0 = bflo(cw), c1 = bfhi(cw);
        const float s0 = __fdividef(c0, 1.f + __expf(fminf(-c0, 80.f))), s1 = __fdividef(c1, 1.f + __expf(fminf(-c1, 80.f)));
        uint32_t hi, lo; split2(s0, s1, hi, lo);
        const uint32_t a = sb + S_SC + (tid >> 4) * 128 + vpos((tid & 15) * 2);
        sts1(a, hi); sts1(a + 64, lo);
    }
    bar_sync(1, NTHR - 64);
    if (warp == 7) bar_arrive(8, 64); else if (warp == 6) bar_arrive(11, 64);

    const uint32_t vlane = (g & 1) * 64 + q * 16;

    {
        float d0[4] = {0.f, 0.f, 0.f, 0.f}, d1[4] = {0.f, 0.f, 0.f, 0.f};
        mbar_wait(bars + C_MOD1 * 8);
        step32(sb + S_MOD1 + warp * 1024, sb + S_SC + ((b & 1) * 8 + warp) * 128 + vlane, lane, d0, d1);
        reduce16_publish(sb, d0, d1, tid, warp, lane, sp + G_H1 + spread((b & 1) * 4096 + (b >> 1) * 64), tg);
    }
    float mean1, rstd1;
    {
        const uint32_t w[8] = {xa.x, xa.y, xa.z, xa.w, xb.x, xb.y, xb.z, xb.w};
        float s = 0.f;
#pragma unroll
        for (int i = 0; i < 8; i++) s += bflo(w[i]) + bfhi(w[i]);
#pragma unroll
        for (int o = 16; o; o >>= 1) s += __shfl_xor_sync(~0u, s, o);
        mean1 = s * (1.f / 512.f);
        float v = 0.f;
#pragma unroll
        for (int i = 0; i < 8; i++) { float a = bflo(w[i]) - mean1, c = bfhi(w[i]) - mean1; v += a * a + c * c; }
#pragma unroll
        for (int o = 16; o; o >>= 1) v += __shfl_xor_sync(~0u, v, o);
        rstd1 = rsqrtf(v * (1.f / 512.f) + 1e-5f);
    }
    if (tid < 128) {
        const unsigned char* s0 = sp + G_H1 + j * 512 + tid * 4;
        const unsigned char* s1 = s0 + 8192;
        uint4 a; int it = 0;
        wait_until(t_start, p.tm[T_H1]);
#pragma unroll 1
        do {
            a.x = ldr1(s0); a.y = ldr1(s1); a.z = ldr1(s0 + 2048); a.w = ldr1(s1 + 2048);
            SPIN_CHECK(it);
        } while (bad4(a, tg) & 1);
        const float hv = (xm - mean1) * rstd1 * (1.f + (u2f(a.z) + u2f(a.w))) + (u2f(a.x) + u2f(a.y));
        uint32_t hi, lo; split2(hv, 0.f, hi, lo);
        const uint32_t ad = sb + S_VEC + (tid >> 5) * 128 + vpos(tid & 31);
        stsh(ad, hi); stsh(ad + 64, lo);
    }
    bar_sync(2, 256);
    {
        float r0, r1;
        gemv128<true>(sb + S_WQ, sb + S_VEC, bars + C_WQ * 8, warp, lane, r0, r1);
        const float t0 = __shfl_sync(~0u, r0, lane & 28), t1 = __shfl_sync(~0u, r1, lane & 28);
        str1(sp + G_H2 + spread(b * 512 + warp * 64 + (q & 1) * 32 + g * 4) + (q >> 1) * 4096, tagf((q & 1) ? t1 : t0, tg));
    }
    mbar_wait(bars + B_BETA * 8);
    const uint32_t beta = lds1(sb + S_EP + 4);
    bar_sync(2, 256);
    if (tid < 128) {
        const unsigned char* src = sp + pick(G_H2 + spread(h * 2048 + tid * 4), beta);
        uint4 a; int it = 0;
#pragma unroll 1
        do {
            a.x = ldr1(src); a.y = ldr1(src + 512); a.z = ldr1(src + 1024); a.w = ldr1(src + 1536);
            SPIN_CHECK(it);
        } while (bad4(a, tg) & 1);
        const float qv = ((u2f(a.x) + u2f(a.y)) + (u2f(a.z) + u2f(a.w))) * (0.08838834764831845f * 1.4426950408889634f);
        uint32_t hi, lo; split2(qv, 0.f, hi, lo);
        const uint32_t ad = sb + S_VEC + (tid >> 5) * 128 + vpos(tid & 31);
        stsh(ad, hi); stsh(ad + 64, lo);
    }
    bar_sync(2, 256);
    {
        float r0, r1;
        gemv128<false>(sb + S_WUK, sb + S_VEC, bars + C_WUK * 8, warp, lane, r0, r1);
        const float n0 = __shfl_down_sync(~0u, r0, 4), m0 = __shfl_up_sync(~0u, r1, 4);
        const uint32_t w = (g & 1) ? packbf(m0, r1) : packbf(r0, n0);
        const uint32_t w2 = __shfl_sync(~0u, w, lane & 28);
        if (q < 2) {
            const int chunk = ((warp & 3) * 2 + (g & 1)) ^ (h & 7);
            str1(sp + G_H3 + (j * 2 + (warp >> 2)) * 8192 + q * 4096 + h * 128 + chunk * 16 + (g >> 1) * 4, w2 ^ 0xFFFF0000u);
        }
        if (lane == 0) mbar_arrive(bars + B_UK * 8);
    }
    {
        const unsigned char* src[6];
#pragma unroll
        for (int i = 0; i < 6; i++) src[i] = sp + pick(G_H3 + (i < 4 ? rank * 4 + i : (rank ^ 1) * 4 + i - 2) * 8192 + tid * 16, beta);
        uint4 v[6];
        wait_until(t_start, p.tm[T_H3]);
#pragma unroll
        for (int i = 0; i < 6; i++) v[i] = ldr4(src[i]);
        int it = 0;
#pragma unroll 1
        while (true) {
            bool ok = true;
#pragma unroll
            for (int i = 0; i < 6; i++) if (!nz4(v[i])) { v[i] = ldr4(src[i]); ok = false; }
            if (__all_sync(~0u, ok)) break;
            SPIN_CHECK(it);
        }
#pragma unroll
        for (int i = 0; i < 6; i++)
            sts4(sb + S_QABS + i * 4096 + tid * 16, v[i].x ^ 0xFFFF0000u, v[i].y ^ 0xFFFF0000u, v[i].z ^ 0xFFFF0000u, v[i].w ^ 0xFFFF0000u);
        fence_async();
        bar_sync(2, 256);
    }
    if (wg) {
        uint32_t bw; int it = 0;
#pragma unroll 1
        do { bw = ldr1(sp + G_H4 + 65536 + 128 + ((tid & 127) >> 1) * 131072 + (tid & 1) * 256); SPIN_CHECK(it); } while (__any_sync(~0u, (bw ^ tg) & 1));
        const uint32_t mb = __ballot_sync(~0u, bw & 2), mt = __ballot_sync(~0u, bw & 4);
        if (lane == 0) sts2(sb + S_B4 + wq * 8, mb, mt);
    }
    if (b < NFFN) {
        unsigned char* d7 = sp + G_H7 + (tid >> 2) * 8192 + b * 32 + (tid & 3) * 8;
        str2(d7, tg ^ 1, tg ^ 1); str2(d7 + 4096, tg ^ 1, tg ^ 1);
    }
    {
        float s[16];
#pragma unroll
        for (int i = 0; i < 16; i++) s[i] = 0.f;
        const uint32_t xo = (wg ? S_XBUF1 : S_XBUF0) + (tid & 127) * 16;
#pragma unroll 1
        for (int cg = 0; cg < 4 - 2 * wg; cg++) {
            mbar_wait(bars + (C_CKV + wg * 4 + cg) * 8);
            const uint64_t da = mkdesc(sb + S_CKV + (wg * 4 + cg) * 8192), db = mkdesc(sb + S_QABS + cg * 4096);
            wg_fence();
#pragma unroll
            for (int k = 0; k < 4; k++) wgmma_n32<0>(s, da + k * 2, db + k * 2, 1);
            wg_commit();
        }
        wg_wait<0>();
        reg_fence16(s);
        {
            uint32_t ra, rb;
            asm("mapa.shared::cluster.u32 %0, %1, %2;" : "=r"(ra) : "r"(sb + xo), "r"(rank ^ 1));
            asm("mapa.shared::cluster.u32 %0, %1, %2;" : "=r"(rb) : "r"(bars + (B_X + wg) * 8), "r"(rank ^ 1));
#pragma unroll
            for (int i = 0; i < 4; i++)
                asm volatile("st.async.weak.shared::cluster.mbarrier::complete_tx::bytes.v4.f32 [%0], {%1,%2,%3,%4}, [%5];"
                             ::"r"(ra + i * 2048), "f"(s[4 * i]), "f"(s[4 * i + 1]), "f"(s[4 * i + 2]), "f"(s[4 * i + 3]), "r"(rb) : "memory");
        }
        float4 xs[4];
#define QK_TAIL(c) do { \
            mbar_wait2(bars + (C_T1 + 2 * (c)) * 8); \
            const uint64_t da = mkdesc(sb + S_CKV + (6 + (c)) * 8192), dx = mkdesc(sb + S_XCH + (c) * 8192), db = mkdesc(sb + S_QABS + (2 + (c)) * 4096); \
            wg_fence(); \
            _Pragma("unroll") for (int k = 0; k < 4; k++) { wgmma_n32<0>(s, da + k * 2, db + k * 2, 1); wgmma_n32<0>(s, dx + k * 2, db + 512 + k * 2, 1); } \
            wg_commit(); } while (0)
        if (wg) QK_TAIL(0);
        mbar_wait_cluster(bars + (B_X + wg) * 8);
#pragma unroll
        for (int i = 0; i < 4; i++) xs[i] = lds4f(sb + xo + i * 2048);
        if (wg) QK_TAIL(1);
        wg_wait<0>();
        reg_fence16(s);
#pragma unroll
        for (int i = 0; i < 4; i++) { s[4 * i] += xs[i].x; s[4 * i + 1] += xs[i].y; s[4 * i + 2] += xs[i].z; s[4 * i + 3] += xs[i].w; }
        const bool b2 = lane & 16, b1 = lane & 8, b0 = lane & 4;
        {
            float v[8];
#pragma unroll
            for (int i = 0; i < 4; i++) { v[2 * i] = fmaxf(s[4 * i], s[4 * i + 2]); v[2 * i + 1] = fmaxf(s[4 * i + 1], s[4 * i + 3]); }
            float u[4];
#pragma unroll
            for (int k = 0; k < 4; k++) u[k] = fmaxf(b2 ? v[k + 4] : v[k], __shfl_xor_sync(~0u, b2 ? v[k] : v[k + 4], 16));
            float t[2];
#pragma unroll
            for (int k = 0; k < 2; k++) t[k] = fmaxf(b1 ? u[k + 2] : u[k], __shfl_xor_sync(~0u, b1 ? u[k] : u[k + 2], 8));
            const uint32_t r = ordf(__float_as_uint(fmaxf(b0 ? t[1] : t[0], __shfl_xor_sync(~0u, b0 ? t[0] : t[1], 4))));
            const uint32_t a = sb + S_MAX + (8 * (g >> 1) + 2 * q + (g & 1)) * 4;
            red_max(a + 128, r);
            if (wg == 0) red_max(a, r);
        }
        if (wg == 0) { bar_arrive(4, 256); bar_sync(3, 128); } else { bar_arrive(7, 256); bar_sync(4, 256); }
        uint32_t pk[8];
#pragma unroll
        for (int i = 0; i < 4; i++) {
            const float2 mm = lds2f(sb + S_MAX + wg * 128 + (8 * i + 2 * q) * 4);
            const float m0 = u2f(ordf(__float_as_uint(mm.x))), m1 = u2f(ordf(__float_as_uint(mm.y)));
            pk[2 * i] = packbf(ex2(s[4 * i] - m0), ex2(s[4 * i + 1] - m1));
            pk[2 * i + 1] = packbf(ex2(s[4 * i + 2] - m0), ex2(s[4 * i + 3] - m1));
        }
        {
            const int t = lane >> 3, r8 = lane & 7;
            const uint32_t a = sb + S_P + wg * 4096 + ((t >> 1) * 8 + r8) * 128 + (((2 * wq + (t & 1)) ^ r8) << 4);
            stsm4t(a, pk[0], pk[1], pk[2], pk[3]);
            stsm4t(a + 2048, pk[4], pk[5], pk[6], pk[7]);
        }
        fence_async();
        if (wg) {
            bar_arrive(5, 256);
            if (warp == 4) {
                str1(sp + G_ML + spread(pair * 256 + lane * 4) + rank * 4096, tagf(u2f(ordf(lds1(sb + S_MAX + 128 + lane * 4))), tg));
                if (lane == 0) mbar_arrive(bars + B_QK * 8);
            }
        } else {
            float o0[16], o1[16], o2[16], o3[16], ol[16];
            const uint64_t d1 = mkdesc(sb + S_ONES) & ~(0x3FFFull << 32);
            const uint64_t db = mkdesc(sb + S_P), da = mkdesc(sb + S_CKV);
            bar_sync(3, 128);
            wg_fence();
#pragma unroll
            for (int k = 0; k < 4; k++) {
                wgmma_n32<1>(o0, da + k * 128, db + k * 2, k);
                wgmma_n32<1>(o1, da + 512 + k * 128, db + k * 2, k);
                wgmma_n32<1>(o2, da + 1024 + k * 128, db + k * 2, k);
                wgmma_n32<1>(o3, da + 1536 + k * 128, db + k * 2, k);
                wgmma_n32<0>(ol, d1, db + k * 2, k);
            }
            wg_commit();
            wg_wait<0>();
            reg_fence16(o0); reg_fence16(o1); reg_fence16(o2); reg_fence16(o3); reg_fence16(ol);
            bar_sync(7, 256);
            {
                const float al = ex2(u2f(ordf(lds1(sb + S_MAX + lane * 4))) - u2f(ordf(lds1(sb + S_MAX + 128 + lane * 4))));
#pragma unroll
                for (int i = 0; i < 4; i++) {
                    const float a0 = __shfl_sync(~0u, al, 8 * i + 2 * q), a1 = __shfl_sync(~0u, al, 8 * i + 2 * q + 1);
                    o0[4 * i] *= a0; o0[4 * i + 1] *= a1; o0[4 * i + 2] *= a0; o0[4 * i + 3] *= a1;
                    o1[4 * i] *= a0; o1[4 * i + 1] *= a1; o1[4 * i + 2] *= a0; o1[4 * i + 3] *= a1;
                    o2[4 * i] *= a0; o2[4 * i + 1] *= a1; o2[4 * i + 2] *= a0; o2[4 * i + 3] *= a1;
                    o3[4 * i] *= a0; o3[4 * i + 1] *= a1; o3[4 * i + 2] *= a0; o3[4 * i + 3] *= a1;
                    ol[4 * i] *= a0; ol[4 * i + 1] *= a1; ol[4 * i + 2] *= a0; ol[4 * i + 3] *= a1;
                }
            }
            mbar_wait(bars + B_BETA4 * 8);
            const uint32_t rec = lds1(sb + S_EP + 8), tg4w = rec >> 2 & 1;
            unsigned char* const h4dst = sp + pick(G_H4 + pair * 131072 + spread(q * 2048 + wq * 256 + rank * 128 + g * 8), rec >> 1);
            unsigned char* ldst = sp + G_ML + spread(pair * 256 + 128 + wq * 32 + q * 8) + rank * 4096;
            PIN(ldst);
            bar_sync(5, 256);
            wg_fence();
#pragma unroll
            for (int k = 0; k < 4; k++) {
                wgmma_n32<1>(o0, da + 2048 + k * 128, db + 256 + k * 2, 1);
                wgmma_n32<1>(o1, da + 2048 + 512 + k * 128, db + 256 + k * 2, 1);
            }
            wg_commit();
            wg_wait<0>();
            reg_fence16(o0); reg_fence16(o1);
            wg_fence();
#pragma unroll
            for (int k = 0; k < 4; k++) wgmma_n32<1>(o2, da + 2048 + 1024 + k * 128, db + 256 + k * 2, 1);
            wg_commit();
#define O_STORE(A, B, OFF) _Pragma("unroll") for (int i = 0; i < 4; i++) _Pragma("unroll") for (int e = 0; e < 2; e++) { \
                const float f0 = u2f((__float_as_uint(A[4 * i + e]) + 0x10000u) & 0xFFFE0000u); \
                str64(h4dst + (OFF) + i * 16384 + e * 1024, packbf(f0, A[4 * i + 2 + e]) | tg4w, packbf(B[4 * i + e], B[4 * i + 2 + e])); }
            O_STORE(o0, o1, 0);
            __syncwarp();
            wg_fence();
#pragma unroll
            for (int k = 0; k < 4; k++) {
                wgmma_n32<1>(o3, da + 2048 + 1536 + k * 128, db + 256 + k * 2, 1);
                wgmma_n32<0>(ol, d1, db + 256 + k * 2, 1);
            }
            wg_commit();
            wg_wait<0>();
            reg_fence16(o2); reg_fence16(o3); reg_fence16(ol);
            {
                const float l0 = (wq & 2) ? ((wq & 1) ? ol[12] : ol[8]) : ((wq & 1) ? ol[4] : ol[0]);
                const float l1 = (wq & 2) ? ((wq & 1) ? ol[13] : ol[9]) : ((wq & 1) ? ol[5] : ol[1]);
                if (g == 0) str2(ldst, tagf(l0, tg), tagf(l1, tg));
            }
            O_STORE(o2, o3, 64);
            if (lane == 0) mbar_arrive(bars + B_O * 8);
        }
    }
    const uint32_t t_o = clk32();
    uint32_t af[8][4];
    {
        const int sg = wq * 4 + (lane >> 3), ur = (lane >> 2) & 1;
        const int po = ur * 128 + (wg ^ 1) * 64 + q * 16;
        uint32_t a0;
        {
            const int m = lane >> 3, r8 = lane & 7;
            const int row = (m >> 1) * 16 + (r8 >> 1) * 2 + (r8 & 1) * 8;
            a0 = sb + S_WUV + wg * 4096 + row * 128 + (((wq * 2 + (m & 1)) ^ (row & 7)) << 4);
        }
        const unsigned char* src[4];
        uint32_t tg4[4];
#pragma unroll
        for (int i = 0; i < 4; i++) {
            const float2 m = lds2f(sb + S_B4 + i * 8);
            src[i] = sp + pick(G_H4 + (sg + 16 * i) * 131072 + spread(b * 256 + po), __float_as_uint(m.x) >> (sg * 2 + ur));
            tg4[i] = __float_as_uint(m.y) >> (sg * 2 + ur);
        }
        uint4 v[4];
        uint32_t have = 0;
        int it = 0;
        unsigned char* d5 = sp + G_H5 + spread(b * 512 + warp * 64 + (q & 1) * 32 + g * 4) + (q >> 1) * 4096;
        PIN(d5);
        if (wg) mbar_wait(bars + B_O * 8);
        wait_until(wg ? clk32() - p.tm[A_H4] : t_o, p.tm[D_H4]);
        wait_until(t_start, p.tm[T_H4] - (wg ? p.tm[A_H4] : 0));
#pragma unroll
        for (int i = 0; i < 4; i++) v[i] = ldr64x2(src[i]);
#define LOAD_UV(now) _Pragma("unroll") for (int i = 0; i < 4; i++) \
            if ((now) >> i & 1) { ldsm4t(a0 + i * 8192, af[2 * i]); ldsm4t((a0 + i * 8192 + 128) ^ 16, af[2 * i + 1]); }
        have = mbar_mask4(bars + C_WUV * 8);
        LOAD_UV(have);
        mbar_wait(bars + B_W * 8);
        float wt[4];
#pragma unroll
        for (int i = 0; i < 4; i++) wt[i] = lds1f(sb + S_ML + (sg + 16 * i) * 4);
#pragma unroll 1
        while (__any_sync(~0u, (or3(xo2(v[0].x, v[0].z, tg4[0]), xo2(v[1].x, v[1].z, tg4[1]), xo2(v[2].x, v[2].z, tg4[2])) | xo2(v[3].x, v[3].z, tg4[3])) & 1)) {
#pragma unroll
            for (int i = 0; i < 4; i++) if (xo2(v[i].x, v[i].z, tg4[i]) & 1) v[i] = ldr64x2(src[i]);
            SPIN_CHECK(it);
        }
        float acc[8] = {0.f, 0.f, 0.f, 0.f, 0.f, 0.f, 0.f, 0.f};
#pragma unroll
        for (int i = 0; i < 4; i++) {
            const uint32_t w[4] = {v[i].x & ~1u, v[i].y, v[i].z & ~1u, v[i].w};
#pragma unroll
            for (int k = 0; k < 4; k++) {
                acc[2 * k] = fmaf(wt[i], bflo(w[k]), acc[2 * k]);
                acc[2 * k + 1] = fmaf(wt[i], bfhi(w[k]), acc[2 * k + 1]);
            }
        }
        {
            const bool u16 = lane & 16, u8 = lane & 8;
            float r[4];
#pragma unroll
            for (int k = 0; k < 4; k++) r[k] = (u16 ? acc[k + 4] : acc[k]) + __shfl_xor_sync(~0u, u16 ? acc[k] : acc[k + 4], 16);
            const float t0 = (u8 ? r[2] : r[0]) + __shfl_xor_sync(~0u, u8 ? r[0] : r[2], 8);
            const float t1 = (u8 ? r[3] : r[1]) + __shfl_xor_sync(~0u, u8 ? r[1] : r[3], 8);
            uint32_t hi, lo; split2(t0, t1, hi, lo);
            const uint32_t a = sb + S_RED + wq * 320 + po + (u16 ? 8 : 0) + (u8 ? 4 : 0);
            sts1(a, hi); sts1(a + 4 * 320, lo);
        }
        bar_sync(2, 256);
        uint4 bq[4];
#pragma unroll
        for (int i = 0; i < 4; i++) bq[i] = lds4(sb + S_RED + g * 320 + i * 64 + q * 16);
        if (have != 15) { mbar_wait4(bars + C_WUV * 8); LOAD_UV(~have); }
        float d[4][4];
#pragma unroll
        for (int i = 0; i < 4; i++) {
            d[i][0] = d[i][1] = d[i][2] = d[i][3] = 0.f;
            mma16816(d[i], af[2 * i], bq[i].x, bq[i].y);
            mma16816(d[i], af[2 * i + 1], bq[i].z, bq[i].w);
        }
        const float r0 = ((d[0][0] + d[0][1]) + (d[1][0] + d[1][1])) + ((d[2][0] + d[2][1]) + (d[3][0] + d[3][1]));
        const float r1 = ((d[0][2] + d[0][3]) + (d[1][2] + d[1][3])) + ((d[2][2] + d[2][3]) + (d[3][2] + d[3][3]));
        float r = ((q & 1) ? r1 : r0) + __shfl_xor_sync(~0u, (q & 1) ? r0 : r1, 1);
        r += __shfl_xor_sync(~0u, r, 2);
        str1(d5, tagf(r, tg));
    }
    const uint32_t t_e = clk32();
    const unsigned char* sm[4];
    uint2 mm[6];
#pragma unroll
    for (int i = 0; i < 4; i++) sm[i] = sp + pick(G_MOD2 + i * 8192 + tid * 8, beta);
#define LOAD_MM() do { mm[0] = ldr2(sm[0]); mm[1] = ldr2(sm[0] + 2048); mm[2] = ldr2(sm[1]); mm[3] = ldr2(sm[2]); mm[4] = ldr2(sm[2] + 2048); mm[5] = ldr2(sm[3]); } while (0)
#define BAD_MM() or3(or3(bad2(mm[0], tg), bad2(mm[1], tg), bad2(mm[2], tg)), or3(bad2(mm[3], tg), bad2(mm[4], tg), bad2(mm[5], tg)), 0)
    {
        const int m = lane >> 3, r8 = lane & 7;
        const uint32_t a0 = sb + S_WO + (warp >> 1) * 2048 + ((m >> 1) * 8 + r8) * 64 + ((((warp & 1) * 2 + (m & 1)) ^ (r8 >> 1)) << 4);
        const unsigned char* src = sp + pick(G_H5 + spread(((b >> 4) * 4 + (warp >> 1)) * 2048 + (tid & 63) * 8), beta);
        uint2 c0, c1, c2, c3; int it = 0;
        uint32_t have = 0;
        unsigned char* d6 = sp + G_H6 + spread(b * 128 + lane * 4) + (warp & 1) * 4096;
        PIN(d6);
        wait_until(t_e, p.tm[D_H5]);
#pragma unroll 1
        do {
            c0 = ldr2(src); c1 = ldr2(src + 512); c2 = ldr2(src + 1024); c3 = ldr2(src + 1536);
            const uint32_t now = mbar_mask4(bars + C_WO * 8) & ~have;
#pragma unroll
            for (int i = 0; i < 4; i++)
                if (now >> i & 1) { ldsm4t(a0 + i * 8192, af[2 * i]); ldsm4t(a0 + i * 8192 + 1024, af[2 * i + 1]); }
            have |= now;
            SPIN_CHECK(it);
        } while (__any_sync(~0u, or3(or3(bad2(c0, tg), bad2(c1, tg), bad2(c2, tg)), bad2(c3, tg), 0) & 1));
        uint32_t hi, lo;
        split2((u2f(c0.x) + u2f(c1.x)) + (u2f(c2.x) + u2f(c3.x)), (u2f(c0.y) + u2f(c1.y)) + (u2f(c2.y) + u2f(c3.y)), hi, lo);
        const uint32_t a = sb + S_FVEC + (tid >> 4) * 128 + vpos((tid & 15) * 2);
        sts1(a, hi); sts1(a + 64, lo);
        bar_sync(2, 256);
        if (b < NFFN) LOAD_MM();
        uint4 bq[4];
#pragma unroll
        for (int i = 0; i < 4; i++) bq[i] = lds4(sb + S_FVEC + (i * 4 + (warp >> 1)) * 128 + vlane);
        if (have != 15) {
#pragma unroll
            for (int i = 0; i < 4; i++)
                if (!(have >> i & 1)) {
                    mbar_wait(bars + (C_WO + i) * 8);
                    ldsm4t(a0 + i * 8192, af[2 * i]); ldsm4t(a0 + i * 8192 + 1024, af[2 * i + 1]);
                }
        }
        float d[4][4];
#pragma unroll
        for (int i = 0; i < 4; i++) {
            d[i][0] = d[i][1] = d[i][2] = d[i][3] = 0.f;
            mma16816(d[i], af[2 * i], bq[i].x, bq[i].y);
            mma16816(d[i], af[2 * i + 1], bq[i].z, bq[i].w);
        }
        {
            const uint32_t o = sb + (q ? S_RED + tid * 4 : S_R16 + ((warp & 1) * 16 + g) * 16 + (warp >> 1) * 4);
            sts1f(o, ((d[0][0] + d[0][1]) + (d[1][0] + d[1][1])) + ((d[2][0] + d[2][1]) + (d[3][0] + d[3][1])));
            sts1f(o + 128, ((d[0][2] + d[0][3]) + (d[1][2] + d[1][3])) + ((d[2][2] + d[2][3]) + (d[3][2] + d[3][3])));
        }
        bar_sync(2, 256);
        if (tid < 64) {
            const float4 u = lds4f(sb + S_R16 + lane * 16);
            str1(d6, tagf((u.x + u.y) + (u.z + u.w), tg));
        }
        if (tid == 64) mbar_arrive(bars + B_F * 8);
        if (tid >= 224) str4(sp + G_H3 + (j * 2 + ((tid >> 3) & 1)) * 8192 + (tid & 16) * 256 + h * 128 + (tid & 7) * 16, 0, 0, 0, 0);
    }
    const uint32_t t_f = clk32();
    if (b < NFFN) {
        const uint32_t ga_ = sb + S_GVEC + (warp * 2 + (lane >> 4)) * 512 + vpos((lane & 15) * 2);
        const int m = lane >> 3, r8 = lane & 7;
        const uint32_t a0 = sb + S_W1 + warp * 2048 + ((m >> 1) * 8 + r8) * 32 + (((m & 1) ^ (r8 >> 2)) << 4);
        bool have1 = false;
        unsigned char* d7 = sp + G_H7 + (tid >> 2) * 8192 + b * 32 + (tid & 3) * 8;
        PIN(d7);
        float x20, x21;
        {
            const unsigned char* so[4];
#pragma unroll
            for (int i = 0; i < 4; i++) so[i] = sp + pick(G_H6 + i * 8192 + tid * 8, beta);
            uint2 c[8]; int it = 0;
            float g0, g1;
#define STAGE_MM() do { \
                g0 = 1.f + (u2f(mm[2].x) + u2f(mm[5].x)); g1 = 1.f + (u2f(mm[2].y) + u2f(mm[5].y)); \
                uint32_t hi, lo; \
                split2(g0, g1, hi, lo); sts1(ga_ + 128, hi); sts1(ga_ + 192, lo); \
                split2(u2f(mm[1].x) + u2f(mm[4].x), u2f(mm[1].y) + u2f(mm[4].y), hi, lo); sts1(ga_ + 256, hi); sts1(ga_ + 320, lo); } while (0)
#pragma unroll 1
            while (BAD_MM() & 1) { LOAD_MM(); SPIN_CHECK(it); }
            STAGE_MM();
            have1 = mbar_mask4(bars + C_W1 * 8) >> wg & 1;
            if (have1) {
#pragma unroll
                for (int i = 0; i < 4; i++) ldsm4t(a0 + i * 512, af[i]);
            }
            wait_until(t_f, p.tm[D_H6]);
#pragma unroll 1
            while (true) {
#pragma unroll
                for (int i = 0; i < 8; i++) c[i] = ldr2(so[i >> 1] + (i & 1) * 2048);
                uint32_t bc = 0;
                bc = or3(or3(bad2(c[0], tg), bad2(c[1], tg), bad2(c[2], tg)), or3(bad2(c[3], tg), bad2(c[4], tg), bad2(c[5], tg)),
                         or3(bad2(c[6], tg), bad2(c[7], tg), bc));
                if (!__any_sync(~0u, bc & 1)) break;
                SPIN_CHECK(it);
            }
            x20 = fmaf(u2f(mm[0].x) + u2f(mm[3].x),
                       ((u2f(c[0].x) + u2f(c[1].x)) + (u2f(c[2].x) + u2f(c[3].x))) + ((u2f(c[4].x) + u2f(c[5].x)) + (u2f(c[6].x) + u2f(c[7].x))), bflo(xw2));
            x21 = fmaf(u2f(mm[0].y) + u2f(mm[3].y),
                       ((u2f(c[0].y) + u2f(c[1].y)) + (u2f(c[2].y) + u2f(c[3].y))) + ((u2f(c[4].y) + u2f(c[5].y)) + (u2f(c[6].y) + u2f(c[7].y))), bfhi(xw2));
            uint32_t hi, lo;
            split2(x20 * g0, x21 * g1, hi, lo); sts1(ga_, hi); sts1(ga_ + 64, lo);
            split2(x20, x21, hi, lo); sts1(ga_ + 384, hi); sts1(ga_ + 448, lo);
            if ((tid >> 2) == b) sts2(sb + S_X2 + (tid & 3) * 8, __float_as_uint(x20), __float_as_uint(x21));
        }
        __syncwarp();
        const uint32_t va = sb + S_GVEC + warp * 1024 + g * 64 + q * 16;
        const uint4 bq0 = lds4(va), bq1 = lds4(va + 512);
        if (!have1) {
            mbar_wait(bars + (C_W1 + wg) * 8);
#pragma unroll
            for (int i = 0; i < 4; i++) ldsm4t(a0 + i * 512, af[i]);
        }
        float d0[4] = {0.f, 0.f, 0.f, 0.f}, d1[4] = {0.f, 0.f, 0.f, 0.f}, d2[4] = {0.f, 0.f, 0.f, 0.f}, d3[4] = {0.f, 0.f, 0.f, 0.f};
        mma16816(d0, af[0], bq0.x, bq0.y); mma16816(d1, af[1], bq0.z, bq0.w);
        mma16816(d2, af[2], bq1.x, bq1.y); mma16816(d3, af[3], bq1.z, bq1.w);
        float e0[4] = {0.f, 0.f, 0.f, 0.f}, e1[4] = {0.f, 0.f, 0.f, 0.f};
        {
            const uint32_t one = 0x3F803F80u;
            const uint32_t t0[4] = {bq0.x, one, bq0.y, one}, t1[4] = {bq0.z, one, bq0.w, one};
            const uint32_t t2[4] = {bq1.x, one, bq1.y, one}, t3[4] = {bq1.z, one, bq1.w, one};
            mma16816(e0, t0, bq0.x, bq0.y); mma16816(e1, t1, bq0.z, bq0.w);
            mma16816(e0, t2, bq1.x, bq1.y); mma16816(e1, t3, bq1.z, bq1.w);
        }
        {
            const bool st = q == 3;
            const float lo_ = fsel(st, (e0[0] + e0[1]) + (e1[0] + e1[1]), ((d0[0] + d0[1]) + (d1[0] + d1[1])) + ((d2[0] + d2[1]) + (d3[0] + d3[1])));
            const float hi_ = fsel(st, (e0[2] + e0[3]) + (e1[2] + e1[3]), ((d0[2] + d0[3]) + (d1[2] + d1[3])) + ((d2[2] + d2[3]) + (d3[2] + d3[3])));
            sts1f(sb + S_RED + q * 512 + g * 32 + warp * 4, lo_);
            sts1f(sb + S_RED + q * 512 + (g + 8) * 32 + warp * 4, hi_);
        }
        bar_arrive(9, 288);
        uint32_t w2r[16];
        mbar_wait2(bars + C_W2 * 8);
#pragma unroll
        for (int r = 0; r < 16; r++) w2r[r] = lds1(sb + S_W2 + r * 1024 + tid * 4);
        float w2f[32];
#pragma unroll
        for (int r = 0; r < 16; r++) { w2f[2 * r] = bflo(w2r[r]); w2f[2 * r + 1] = bfhi(w2r[r]); }
        bar_sync(10, b < 64 ? 320 : 288);
        float y0a = 0.f, y0b = 0.f, y1a = 0.f, y1b = 0.f;
#pragma unroll
        for (int r = 0; r < 16; r += 4) {
            const float4 f = lds4f(sb + S_STAT + r * 4);
            y0a = fmaf(f.x, w2f[2 * r], y0a); y1a = fmaf(f.x, w2f[2 * r + 1], y1a);
            y0b = fmaf(f.y, w2f[2 * r + 2], y0b); y1b = fmaf(f.y, w2f[2 * r + 3], y1b);
            y0a = fmaf(f.z, w2f[2 * r + 4], y0a); y1a = fmaf(f.z, w2f[2 * r + 5], y1a);
            y0b = fmaf(f.w, w2f[2 * r + 6], y0b); y1b = fmaf(f.w, w2f[2 * r + 7], y1b);
        }
        const uint32_t w0 = tagf(y0a + y0b, tg), w1 = tagf(y1a + y1b, tg);
        str2(d7, w0, w1); str2(d7 + 4096, w0, w1);
    }
}

__global__ void fb_gemv(const float* v, int vs, const __nv_bfloat16* W, size_t ws, size_t ks, size_t ns, int K, int N, float* out, float scale) {
    const int n = blockIdx.x * 8 + (threadIdx.x >> 5), z = blockIdx.y;
    if (n >= N) return;
    float s = 0.f;
    for (int k = threadIdx.x & 31; k < K; k += 32) s += v[(size_t)z * vs + k] * __bfloat162float(W[z * ws + k * ks + n * ns]);
    for (int o = 16; o; o >>= 1) s += __shfl_xor_sync(~0u, s, o);
    if ((threadIdx.x & 31) == 0) out[(size_t)z * N + n] = s * scale;
}
__device__ float fb_block_reduce(float v, bool mx, float* sh) {
    for (int o = 16; o; o >>= 1) { const float t = __shfl_xor_sync(~0u, v, o); v = mx ? fmaxf(v, t) : v + t; }
    __syncthreads();
    if ((threadIdx.x & 31) == 0) sh[threadIdx.x >> 5] = v;
    __syncthreads();
    v = sh[0];
    for (int i = 1; i < 16; i++) v = mx ? fmaxf(v, sh[i]) : v + sh[i];
    return v;
}
__global__ void fb_elem(int step, Params p, float* f) {
    __shared__ float sh[16];
    const int t = threadIdx.x;
    float* sc = f; float* mod = f + 512; float* hh = f + 4096; float* sco = f + 32768; float* o = f + 8192; float* x2 = f + 8704;
    float* ff = f + 9216; float* y = f + 11264;
    if (step == 0) { const float c = __bfloat162float(p.c[t]); sc[t] = c / (1.f + expf(-c)); }
    if (step == 1 || step == 3) {
        float x = __bfloat162float(p.x[t]);
        if (step == 3) { x += mod[1024 + t] * o[t]; x2[t] = x; }
        const float m = fb_block_reduce(x, false, sh) / 512.f, va = fb_block_reduce((x - m) * (x - m), false, sh) / 512.f;
        hh[t] = (x - m) * rsqrtf(va + 1e-5f) * (1.f + mod[(step == 1 ? 512 : 2048) + t]) + mod[(step == 1 ? 0 : 1536) + t];
    }
    if (step == 2) {
        float* r = sco + blockIdx.x * 8192;
        float m = -INFINITY, s = 0.f;
        for (int k = t; k < 8192; k += 512) m = fmaxf(m, r[k]);
        m = fb_block_reduce(m, true, sh);
        for (int k = t; k < 8192; k += 512) { r[k] = expf(r[k] - m); s += r[k]; }
        s = fb_block_reduce(s, false, sh);
        for (int k = t; k < 8192; k += 512) r[k] /= s;
    }
    if (step == 4)
        for (int n = t; n < 1376; n += 512) {
            const float a = ff[n] + __bfloat162float(p.b1[n]);
            ff[n] = 0.5f * a * (1.f + tanhf(0.7978845608f * (a + 0.044715f * a * a * a)));
        }
    if (step == 5) p.out[t] = __float2bfloat16(x2[t] + mod[2560 + t] * (y[t] + __bfloat162float(p.b2[t])));
}
void launch_fallback(const Params& p, void* const* d_in, cudaStream_t st) {
    typedef const __nv_bfloat16* W;
    float* f = reinterpret_cast<float*>(p.s + G_BYTES - (2 << 20) + 0);
    float *sc = f, *mod = f + 512, *hh = f + 4096, *q = f + 12288, *qa = f + 16384, *sco = f + 32768, *cc = f + 16384, *ctx = f + 12288;
    float *o = f + 8192, *ff = f + 9216, *y = f + 11264;
    fb_elem<<<1, 512, 0, st>>>(0, p, f);
    fb_gemv<<<dim3(384, 1), 256, 0, st>>>(sc, 0, (W)d_in[12], 0, 3072, 1, 512, 3072, mod, 1.f);
    fb_elem<<<1, 512, 0, st>>>(1, p, f);
    fb_gemv<<<dim3(512, 1), 256, 0, st>>>(hh, 0, (W)d_in[2], 0, 4096, 1, 512, 4096, q, 1.f);
    fb_gemv<<<dim3(64, 32), 256, 0, st>>>(q, 128, (W)d_in[3], 128, 1, 4096, 128, 512, qa, 0.08838834764831845f);
    fb_gemv<<<dim3(1024, 32), 256, 0, st>>>(qa, 512, (W)d_in[1], 0, 1, 512, 512, 8192, sco, 1.f);
    fb_elem<<<32, 512, 0, st>>>(2, p, f);
    fb_gemv<<<dim3(64, 32), 256, 0, st>>>(sco, 8192, (W)d_in[1], 0, 512, 1, 8192, 512, cc, 1.f);
    fb_gemv<<<dim3(16, 32), 256, 0, st>>>(cc, 512, (W)d_in[4], 128, 4096, 1, 512, 128, ctx, 1.f);
    fb_gemv<<<dim3(64, 1), 256, 0, st>>>(ctx, 0, (W)d_in[5], 0, 512, 1, 4096, 512, o, 1.f);
    fb_elem<<<1, 512, 0, st>>>(3, p, f);
    fb_gemv<<<dim3(172, 1), 256, 0, st>>>(hh, 0, (W)d_in[7], 0, 1376, 1, 512, 1376, ff, 1.f);
    fb_elem<<<1, 512, 0, st>>>(4, p, f);
    fb_gemv<<<dim3(64, 1), 256, 0, st>>>(ff, 0, (W)d_in[9], 0, 512, 1, 1376, 512, y, 1.f);
    fb_elem<<<1, 512, 0, st>>>(5, p, f);
}

typedef CUresult (*EncodeFn)(CUtensorMap*, CUtensorMapDataType, cuuint32_t, void*, const cuuint64_t*, const cuuint64_t*,
                             const cuuint32_t*, const cuuint32_t*, CUtensorMapInterleave, CUtensorMapSwizzle,
                             CUtensorMapL2promotion, CUtensorMapFloatOOBfill);

void make_map(EncodeFn enc, CUtensorMap* m, const void* ptr, uint64_t d0, uint64_t d1, uint64_t d2, uint64_t d3,
              uint64_t s1, uint64_t s2, uint64_t s3, uint32_t b0, uint32_t b1, uint32_t b2, uint32_t b3, CUtensorMapSwizzle sw) {
    cuuint64_t dims[4] = {d0, d1, d2, d3};
    cuuint64_t st[3] = {s1, s2, s3};
    cuuint32_t box[4] = {b0, b1, b2, b3};
    cuuint32_t es[4] = {1, 1, 1, 1};
    enc(m, CU_TENSOR_MAP_DATA_TYPE_BFLOAT16, 4, const_cast<void*>(ptr), dims, st, box, es, CU_TENSOR_MAP_INTERLEAVE_NONE, sw,
        CU_TENSOR_MAP_L2_PROMOTION_L2_128B, CU_TENSOR_MAP_FLOAT_OOB_FILL_NONE);
}

const uint16_t g_tm[NTM] = {3880,7540,14905,350,420,600,900,280};
const uint16_t g_sched[34] = {0,1070,1640,2185,2815,3410,3980,4525,5095,5665,6235,6745,7290,7885,8455,8965,9085,
                        9383,9803,9833,10503,11053,11885,12835,13135,15235,15255,15495,16605,17705,17785,18605,18655,0};

}

extern "C" void kernel_launch(void* const* d_in, const int* in_sizes, int n_in, void* d_out, int out_size) {
    (void)in_sizes; (void)n_in; (void)out_size;
    static EncodeFn enc = nullptr;
    static unsigned char* scratch = nullptr;
    static bool fused_ok = false;
    if (!scratch) {
        cudaGetSymbolAddress((void**)&scratch, g_scratch);
        scratch = (unsigned char*)(((uintptr_t)scratch + (2 << 20) - 1) & ~(uintptr_t)((2 << 20) - 1));
        void* fn = nullptr;
        cudaDriverEntryPointQueryResult qr;
        cudaGetDriverEntryPoint("cuTensorMapEncodeTiled", &fn, cudaEnableDefault, &qr);
        enc = (EncodeFn)fn;
        int clusters = 0;
        if (enc && cudaFuncSetAttribute(fused_decode_kernel, cudaFuncAttributeMaxDynamicSharedMemorySize, SMEM_BYTES) == cudaSuccess) {
            cudaLaunchConfig_t cfg = {};
            cfg.gridDim = dim3(NCTA); cfg.blockDim = dim3(NTHR); cfg.dynamicSmemBytes = SMEM_BYTES;
            cudaLaunchAttribute at[1];
            at[0].id = cudaLaunchAttributeClusterDimension; at[0].val.clusterDim.x = 2; at[0].val.clusterDim.y = 1; at[0].val.clusterDim.z = 1;
            cfg.attrs = at; cfg.numAttrs = 1;
            if (cudaOccupancyMaxActiveClusters(&clusters, fused_decode_kernel, &cfg) != cudaSuccess) clusters = 0;
        }
        (void)cudaGetLastError();
        fused_ok = clusters >= NCTA / 2;
    }
    Params p = {};
    p.x = (const __nv_bfloat16*)d_in[0];
    p.c = (const __nv_bfloat16*)d_in[11];
    p.b1 = (const __nv_bfloat16*)d_in[8];
    p.b2 = (const __nv_bfloat16*)d_in[10];
    p.out = (__nv_bfloat16*)d_out;
    p.s = scratch;
    for (int i = 0; i < NTM; i++) p.tm[i] = g_tm[i];
    for (int i = 0; i < 34; i++) p.sched[i] = g_sched[i];
    if (!fused_ok) { launch_fallback(p, d_in, cudaStreamPerThread); return; }
    const auto S128 = CU_TENSOR_MAP_SWIZZLE_128B, S32 = CU_TENSOR_MAP_SWIZZLE_32B, S64 = CU_TENSOR_MAP_SWIZZLE_64B, S0 = CU_TENSOR_MAP_SWIZZLE_NONE;
    make_map(enc, &p.m[0], d_in[12], 3072, 512, 1, 1, 6144, 6144 * 512, 6144 * 512, 16, 256, 1, 1, S32);
    make_map(enc, &p.m[1], d_in[2], 64, 512, 64, 1, 8192, 128, 8192 * 512, 64, 32, 2, 1, S128);
    make_map(enc, &p.m[2], d_in[3], 64, 512, 64, 1, 8192, 128, 8192 * 512, 64, 32, 2, 1, S128);
    make_map(enc, &p.m[3], d_in[1], 64, 8192, 8, 1, 1024, 128, 1024 * 8192, 64, 64, 1, 1, S128);
    make_map(enc, &p.m[4], d_in[4], 64, 64, 8, 64, 8192, 8192 * 64, 128, 64, 16, 2, 2, S128);
    make_map(enc, &p.m[5], d_in[5], 512, 4096, 1, 1, 1024, 1024 * 4096, 1024 * 4096, 32, 128, 1, 1, S64);
    make_map(enc, &p.m[8], d_in[12], 3072, 512, 1, 1, 6144, 6144 * 512, 6144 * 512, 32, 128, 1, 1, S64);
    make_map(enc, &p.m[6], d_in[7], 1376, 512, 1, 1, 2752, 2752 * 512, 2752 * 512, 16, 256, 1, 1, S32);
    make_map(enc, &p.m[7], d_in[9], 256, 2752, 1, 1, 512, 512 * 2752, 512 * 2752, 256, 16, 1, 1, S0);
    fused_decode_kernel<<<NCTA, NTHR, SMEM_BYTES, cudaStreamPerThread>>>(p);
}
```
